```python
import torch

def _softmax(x, axis=-1):
    return torch.softmax(x, dim=axis)

def _gelu(x):
    return torch.nn.functional.gelu(x, approximate='tanh')

def _silu(x):
    return torch.nn.functional.silu(x)

def _sigmoid(x):
    return torch.sigmoid(x)

def _layernorm(x, axis=-1, eps=1e-05):
    m = x.mean(dim=axis, keepdim=True)
    v = x.var(dim=axis, keepdim=True, unbiased=False)
    return (x - m) / torch.sqrt(v + eps)

def _scatter_add(tgt, idx, src, axis=0):
    return tgt.clone().index_add_(axis, idx, src)

def _segment_sum(src, seg, n):
    out = torch.zeros((n,) + src.shape[1:], dtype=src.dtype)
    return out.index_add_(0, seg, src)

def _pad(x, pw):
    flat = tuple((v for pair in reversed(pw) for v in pair))
    return torch.nn.functional.pad(x, flat)
kernel_name = 'adaLN_cond__spectral_gfnet__dense_activation_silu__prompt'

def setup_inputs():

    _w = lambda a: (lambda t: t.to(torch.bfloat16) if t.is_floating_point() else t)(torch.as_tensor(a))

    def _A_setup():
        B, S, D = (1, 2048, 640)
        Df = D // 2 + 1
        return {'x': _w((lambda *s: torch.randn(*s, dtype=torch.bfloat16) * 0.05)(B, S, D)), 'w_r': _w((lambda *s: torch.randn(*s, dtype=torch.bfloat16) * 3.2)(S, Df) * 0.02), 'w_i': _w((lambda *s: torch.randn(*s, dtype=torch.bfloat16) * 3.2)(S, Df) * 0.02)}
    _A_in = _A_setup()

    def _B_setup():
        B, S, D, F = (1, 2048, 640, 1536)
        return {'x': _w((lambda *s: torch.randn(*s, dtype=torch.bfloat16) * 0.05)(B, S, D)), 'w1': _w((lambda *s: torch.randn(*s, dtype=torch.bfloat16) * 0.8)(D, F) * D ** (-0.5)), 'w2': _w((lambda *s: torch.randn(*s, dtype=torch.bfloat16) * 0.2)(F, D) * F ** (-0.5))}
    _B_in = _B_setup()
    return {'A_x': _A_in['x'], 'A_w_r': _A_in['w_r'], 'A_w_i': _A_in['w_i'], 'B_x': _B_in['x'], 'B_w1': _B_in['w1'], 'B_w2': _B_in['w2'], 'c': _w((lambda *s: torch.randn(*s, dtype=torch.bfloat16) * 0.1)(1, 640) * 8.0), 'w_mod': _w((lambda *s: torch.randn(*s, dtype=torch.bfloat16) * 0.1)(640, 6 * 640) * 640 ** (-0.5) * 8.0)}

def reference(A_x, A_w_r, A_w_i, B_x, B_w1, B_w2, c, w_mod):

    def _A_ref(x, w_r, w_i):
        B, S, D = x.shape
        X = (lambda x, axes=(-2, -1): torch.fft.rfft2(x.float(), dim=axes))(x, axes=(-2, -1))
        W = w_r + 1j * w_i
        X = X * W
        y = (lambda x, s, axes=(-2, -1): torch.fft.irfft2(x, s=s, dim=axes).to(torch.bfloat16))(X, (S, D), axes=(-2, -1))
        return y

    def _B_ref(x, w1, w2):
        h = torch.einsum('bsd,df->bsf', x, w1)
        h = _silu(h)
        out = torch.einsum('bsf,fd->bsd', h, w2)
        return out
    x = A_x
    mod = (_silu(c) @ w_mod).reshape(c.shape[0], 6, 1, -1)
    sa, ca, ga, sb, cb, gb = (mod[:, 0].clone(), mod[:, 1].clone(), mod[:, 2].clone(), mod[:, 3].clone(), mod[:, 4].clone(), mod[:, 5].clone())
    h = _layernorm(x, axis=-1) * (1 + ca) + sa
    x = x + ga * _A_ref(h, A_w_r, A_w_i)
    h = _layernorm(x, axis=-1) * (1 + cb) + sb
    x = x + gb * _B_ref(h, B_w1, B_w2)
    return x
```

```cpp
#include <cuda_runtime.h>
#include <cuda_bf16.h>
#include <cuda.h>
#include <stdint.h>

typedef __nv_bfloat16 bf16;

__device__ float2 g_I[8 * 80 * 128 * 8];
__device__ unsigned long long g_modw[640];
__device__ uint32_t g_mod2[1280];

__device__ __forceinline__ float bf_lo(uint32_t v) { return __uint_as_float(v << 16); }
__device__ __forceinline__ float bf_hi(uint32_t v) { return __uint_as_float(v & 0xffff0000u); }
__device__ __forceinline__ float bf_round(float v) { return __bfloat162float(__float2bfloat16_rn(v)); }
__device__ __forceinline__ uint32_t pack_bf2(float lo, float hi) {
    uint32_t r;
    asm("cvt.rn.bf16x2.f32 %0, %1, %2;" : "=r"(r) : "f"(hi), "f"(lo));
    return r;
}
__device__ __forceinline__ uint32_t ldg_nc32(const void* p) {
    uint32_t r;
    asm volatile("ld.global.nc.L1::no_allocate.b32 %0, [%1];" : "=r"(r) : "l"(p));
    return r;
}
__device__ __forceinline__ uint2 ldg_nc64(const void* p) {
    uint2 r;
    asm volatile("ld.global.nc.L1::no_allocate.v2.b32 {%0,%1}, [%2];" : "=r"(r.x), "=r"(r.y) : "l"(p));
    return r;
}
__device__ __forceinline__ uint4 ldg_nc128(const void* p) {
    uint4 r;
    asm volatile("ld.global.nc.L1::no_allocate.v4.b32 {%0,%1,%2,%3}, [%4];"
                 : "=r"(r.x), "=r"(r.y), "=r"(r.z), "=r"(r.w) : "l"(p));
    return r;
}
__device__ __forceinline__ uint32_t ldg_nc16(const void* p) {
    unsigned short r;
    asm volatile("ld.global.nc.b16 %0, [%1];" : "=h"(r) : "l"(p));
    return (uint32_t)r;
}
__device__ __forceinline__ float2 ldg_cg64(const float2* p) {
    float2 r;
    asm volatile("ld.global.cg.v2.f32 {%0,%1}, [%2];" : "=f"(r.x), "=f"(r.y) : "l"(p));
    return r;
}
__device__ __forceinline__ void pdl_wait() { asm volatile("griddepcontrol.wait;" ::: "memory"); }
__device__ __forceinline__ void pdl_launch() { asm volatile("griddepcontrol.launch_dependents;" ::: "memory"); }
__device__ __forceinline__ float silu_f(float v) { return v / (1.0f + __expf(-v)); }

__device__ __forceinline__ float2 cadd(float2 a, float2 b) { return make_float2(a.x + b.x, a.y + b.y); }
__device__ __forceinline__ float2 csub(float2 a, float2 b) { return make_float2(a.x - b.x, a.y - b.y); }
__device__ __forceinline__ float2 cmul(float2 a, float2 b) {
    return make_float2(fmaf(a.x, b.x, -a.y * b.y), fmaf(a.x, b.y, a.y * b.x));
}
__device__ __forceinline__ float2 cmulc(float2 a, float2 b) {
    return make_float2(fmaf(a.x, b.x, a.y * b.y), fmaf(a.y, b.x, -a.x * b.y));
}
__device__ __forceinline__ float2 twiddle(int num, float inv_half_den) {
    float s, c;
    sincospif((float)num * inv_half_den, &s, &c);
    return make_float2(c, -s);
}

__device__ __forceinline__ void dft4(float2& a0, float2& a1, float2& a2, float2& a3) {
    float2 s0 = cadd(a0, a2), d0 = csub(a0, a2), s1 = cadd(a1, a3), d1 = csub(a1, a3);
    a0 = cadd(s0, s1);
    a2 = csub(s0, s1);
    a1 = make_float2(d0.x + d1.y, d0.y - d1.x);
    a3 = make_float2(d0.x - d1.y, d0.y + d1.x);
}
#define R2 0.70710678118654752440f
#define C16 0.92387953251128675613f
#define S16 0.38268343236508977173f
__device__ __forceinline__ float2 mulW8_1(float2 a) { return make_float2(R2 * (a.x + a.y), R2 * (a.y - a.x)); }
__device__ __forceinline__ float2 mulW8_3(float2 a) { return make_float2(R2 * (a.y - a.x), -R2 * (a.x + a.y)); }
__device__ __forceinline__ float2 mulmi(float2 a) { return make_float2(a.y, -a.x); }

#define O16(k) (4 * ((k) & 3) + ((k) >> 2))
__device__ __forceinline__ void dft16(float2* v) {
#pragma unroll
    for (int n2 = 0; n2 < 4; n2++) dft4(v[n2], v[4 + n2], v[8 + n2], v[12 + n2]);
    v[5] = cmul(v[5], make_float2(C16, -S16));
    v[6] = mulW8_1(v[6]);
    v[7] = cmul(v[7], make_float2(S16, -C16));
    v[9] = mulW8_1(v[9]);
    v[10] = mulmi(v[10]);
    v[11] = mulW8_3(v[11]);
    v[13] = cmul(v[13], make_float2(S16, -C16));
    v[14] = mulW8_3(v[14]);
    v[15] = cmul(v[15], make_float2(-C16, S16));
#pragma unroll
    for (int k1 = 0; k1 < 4; k1++) dft4(v[4 * k1], v[4 * k1 + 1], v[4 * k1 + 2], v[4 * k1 + 3]);
}
#define O8(k) (4 * ((k) & 1) + ((k) >> 1))
__device__ __forceinline__ void dft8(float2& a0, float2& a1, float2& a2, float2& a3, float2& a4, float2& a5,
                                     float2& a6, float2& a7) {
    float2 t;
    t = csub(a0, a4); a0 = cadd(a0, a4); a4 = t;
    t = csub(a1, a5); a1 = cadd(a1, a5); a5 = mulW8_1(t);
    t = csub(a2, a6); a2 = cadd(a2, a6); a6 = mulmi(t);
    t = csub(a3, a7); a3 = cadd(a3, a7); a7 = mulW8_3(t);
    dft4(a0, a1, a2, a3);
    dft4(a4, a5, a6, a7);
}
__device__ __forceinline__ void dft5(float2& x0, float2& x1, float2& x2, float2& x3, float2& x4) {
    const float c1 = 0.30901699437494742410f, c2 = -0.80901699437494742410f;
    const float s1 = 0.95105651629515357212f, s2 = 0.58778525229247312917f;
    float2 t1 = cadd(x1, x4), t2 = cadd(x2, x3), t3 = csub(x1, x4), t4 = csub(x2, x3);
    float2 a1 = make_float2(fmaf(c2, t2.x, fmaf(c1, t1.x, x0.x)), fmaf(c2, t2.y, fmaf(c1, t1.y, x0.y)));
    float2 a2 = make_float2(fmaf(c1, t2.x, fmaf(c2, t1.x, x0.x)), fmaf(c1, t2.y, fmaf(c2, t1.y, x0.y)));
    float2 b1 = make_float2(fmaf(s2, t4.x, s1 * t3.x), fmaf(s2, t4.y, s1 * t3.y));
    float2 b2 = make_float2(fmaf(-s1, t4.x, s2 * t3.x), fmaf(-s1, t4.y, s2 * t3.y));
    x0 = make_float2(x0.x + t1.x + t2.x, x0.y + t1.y + t2.y);
    x1 = make_float2(a1.x + b1.y, a1.y - b1.x);
    x4 = make_float2(a1.x - b1.y, a1.y + b1.x);
    x2 = make_float2(a2.x + b2.y, a2.y - b2.x);
    x3 = make_float2(a2.x - b2.y, a2.y + b2.x);
}
#define SL40(n1, n2) ((5 * (n1) + 8 * (n2)) % 40)
#define K40(k1, k2) ((25 * (k1) + 16 * (k2)) % 40)
__device__ __forceinline__ void dft40(float2* v) {
#pragma unroll
    for (int n1 = 0; n1 < 8; n1++)
        dft5(v[SL40(n1, 0)], v[SL40(n1, 1)], v[SL40(n1, 2)], v[SL40(n1, 3)], v[SL40(n1, 4)]);
#pragma unroll
    for (int k2 = 0; k2 < 5; k2++)
        dft8(v[SL40(0, k2)], v[SL40(1, k2)], v[SL40(2, k2)], v[SL40(3, k2)], v[SL40(4, k2)], v[SL40(5, k2)],
             v[SL40(6, k2)], v[SL40(7, k2)]);
}

__device__ __forceinline__ float warp_reduce16(float* s, int lane) {
#pragma unroll
    for (int i = 0; i < 8; i++) {
        bool up = lane & 16;
        float send = up ? s[i] : s[i + 8], keep = up ? s[i + 8] : s[i];
        s[i] = keep + __shfl_xor_sync(0xffffffffu, send, 16);
    }
#pragma unroll
    for (int i = 0; i < 4; i++) {
        bool up = lane & 8;
        float send = up ? s[i] : s[i + 4], keep = up ? s[i + 4] : s[i];
        s[i] = keep + __shfl_xor_sync(0xffffffffu, send, 8);
    }
#pragma unroll
    for (int i = 0; i < 2; i++) {
        bool up = lane & 4;
        float send = up ? s[i] : s[i + 2], keep = up ? s[i + 2] : s[i];
        s[i] = keep + __shfl_xor_sync(0xffffffffu, send, 4);
    }
    {
        bool up = lane & 2;
        float send = up ? s[0] : s[1], keep = up ? s[1] : s[0];
        s[0] = keep + __shfl_xor_sync(0xffffffffu, send, 2);
    }
    return s[0] + __shfl_xor_sync(0xffffffffu, s[0], 1);
}

#define P1 648
#define P2 664
#define SPIN_LIMIT (1 << 22)

struct K1Smem {
    float2 S1[8 * P1];
    float2 S2[8 * P2];
    float2 tw[15 * 40];
    float2 T[8];
    float red[2][10][16];
    float mred[10][16];
};

__global__ void __launch_bounds__(320, 1)
k1_kernel(const bf16* __restrict__ x, const bf16* __restrict__ c, const bf16* __restrict__ wmod) {
    extern __shared__ __align__(16) unsigned char smem_raw[];
    K1Smem& sm = *reinterpret_cast<K1Smem*>(smem_raw);
    const int t = threadIdx.x, g = blockIdx.x, lane = t & 31, warp = t >> 5;
    pdl_launch();

    uint4 wv[4];
    uint32_t cv[4];
    if (g < 80) {
#pragma unroll
        for (int i = 0; i < 4; i++) {
            int r = (t >> 1) + 160 * i;
            wv[i] = ldg_nc128(wmod + (size_t)r * 3840 + g * 16 + (t & 1) * 8);
            cv[i] = ldg_nc16(c + r);
        }
    }
    uint32_t xr[16];
#pragma unroll
    for (int m = 0; m < 16; m++) xr[m] = ldg_nc32(x + (size_t)(g + 128 * m) * 640 + 2 * t);

    {
        int i = t;
        sm.tw[i] = twiddle((i % 40) * (i / 40 + 1), 2.0f / 640.0f);
        i = t + 320;
        if (i < 600) sm.tw[i] = twiddle((i % 40) * (i / 40 + 1), 2.0f / 640.0f);
        if (t >= 312) sm.T[t - 312] = twiddle(g * (t - 312), 2.0f / 2048.0f);
    }

    if (g < 80) {
        float acc[8];
#pragma unroll
        for (int j = 0; j < 8; j++) acc[j] = 0.f;
#pragma unroll
        for (int i = 0; i < 4; i++) {
            float s = bf_round(silu_f(bf_lo(cv[i])));
            acc[0] = fmaf(s, bf_lo(wv[i].x), acc[0]); acc[1] = fmaf(s, bf_hi(wv[i].x), acc[1]);
            acc[2] = fmaf(s, bf_lo(wv[i].y), acc[2]); acc[3] = fmaf(s, bf_hi(wv[i].y), acc[3]);
            acc[4] = fmaf(s, bf_lo(wv[i].z), acc[4]); acc[5] = fmaf(s, bf_hi(wv[i].z), acc[5]);
            acc[6] = fmaf(s, bf_lo(wv[i].w), acc[6]); acc[7] = fmaf(s, bf_hi(wv[i].w), acc[7]);
        }
#pragma unroll
        for (int i = 0; i < 4; i++) {
            bool up = lane & 16;
            float send = up ? acc[i] : acc[i + 4], keep = up ? acc[i + 4] : acc[i];
            acc[i] = keep + __shfl_xor_sync(0xffffffffu, send, 16);
        }
#pragma unroll
        for (int i = 0; i < 2; i++) {
            bool up = lane & 8;
            float send = up ? acc[i] : acc[i + 2], keep = up ? acc[i + 2] : acc[i];
            acc[i] = keep + __shfl_xor_sync(0xffffffffu, send, 8);
        }
        {
            bool up = lane & 4;
            float send = up ? acc[0] : acc[1], keep = up ? acc[1] : acc[0];
            acc[0] = keep + __shfl_xor_sync(0xffffffffu, send, 4);
        }
        acc[0] += __shfl_xor_sync(0xffffffffu, acc[0], 2);
        if (!(lane & 2)) sm.mred[warp][(lane & 1) * 8 + (lane >> 2)] = acc[0];
        __syncthreads();
        if (t < 8) {
            float a = 0.f, b = 0.f;
#pragma unroll
            for (int w = 0; w < 10; w++) { a += sm.mred[w][2 * t]; b += sm.mred[w][2 * t + 1]; }
            unsigned long long v = (1ull << 32) | (unsigned long long)pack_bf2(a, b);
            asm volatile("st.relaxed.gpu.global.b64 [%0], %1;" ::"l"(&g_modw[g * 8 + t]), "l"(v) : "memory");
        }
    }

    float2 v[16];
    float s[16];
#pragma unroll
    for (int m = 0; m < 16; m++) {
        v[m] = make_float2(bf_lo(xr[m]), bf_hi(xr[m]));
        s[m] = v[m].x + v[m].y;
    }
    {
        float r = warp_reduce16(s, lane);
        if (!(lane & 1)) sm.red[0][warp][lane >> 1] = r;
    }
    __syncthreads();
    float mean_l;
    {
        float r = 0.f;
#pragma unroll
        for (int i = 0; i < 5; i++) r += sm.red[0][(lane & 1) * 5 + i][lane >> 1];
        r += __shfl_xor_sync(0xffffffffu, r, 1);
        mean_l = r * (1.0f / 640.0f);
    }
#pragma unroll
    for (int m = 0; m < 16; m++) {
        float mu = __shfl_sync(0xffffffffu, mean_l, 2 * m);
        float a = v[m].x - mu, b = v[m].y - mu;
        s[m] = a * a + b * b;
    }
    {
        float r = warp_reduce16(s, lane);
        if (!(lane & 1)) sm.red[1][warp][lane >> 1] = r;
    }
    __syncthreads();
    {
        float r = 0.f;
#pragma unroll
        for (int i = 0; i < 5; i++) r += sm.red[1][(lane & 1) * 5 + i][lane >> 1];
        r += __shfl_xor_sync(0xffffffffu, r, 1);
        float var = bf_round(r * (1.0f / 640.0f));
        float den = bf_round(sqrtf(bf_round(var + 1e-5f)));
        float rs = 1.0f / den;
        float mr = bf_round(mean_l) * rs;
#pragma unroll
        for (int m = 0; m < 16; m++) {
            float rr = __shfl_sync(0xffffffffu, rs, 2 * m);
            float mm = __shfl_sync(0xffffffffu, mr, 2 * m);
            v[m] = make_float2(fmaf(v[m].x, rr, -mm), fmaf(v[m].y, rr, -mm));
        }
    }
    dft16(v);
    float4 o[8];
    o[0] = make_float4(v[O16(0)].x, v[O16(8)].x, v[O16(0)].y, v[O16(8)].y);
#pragma unroll
    for (int f = 1; f < 8; f++) {
        float2 zp = v[O16(f)], zm = v[O16(16 - f)];
        float2 T = sm.T[f];
        float2 a0 = cmul(make_float2(zp.x + zm.x, zp.y - zm.y), T);
        float2 a1 = cmul(make_float2(zp.y + zm.y, zm.x - zp.x), T);
        o[f] = make_float4(a0.x, a0.y, a1.x, a1.y);
    }
    {
        unsigned long long wsa, wca;
        int it = 0;
        do {
            asm volatile("ld.relaxed.gpu.global.b64 %0, [%1];" : "=l"(wsa) : "l"(&g_modw[t]) : "memory");
            asm volatile("ld.relaxed.gpu.global.b64 %0, [%1];" : "=l"(wca) : "l"(&g_modw[320 + t]) : "memory");
        } while ((((wsa & wca) >> 32) == 0) && ++it < SPIN_LIMIT);
        uint32_t sa = (uint32_t)wsa, ca = (uint32_t)wca;
        float s0 = 0.5f * bf_round(1.0f + bf_lo(ca)), s1 = 0.5f * bf_round(1.0f + bf_hi(ca));
        o[0] = make_float4(fmaf(o[0].x, s0, 8.0f * bf_lo(sa)), o[0].y * s0, fmaf(o[0].z, s1, 8.0f * bf_hi(sa)),
                           o[0].w * s1);
        *reinterpret_cast<float4*>(&sm.S1[2 * t]) = o[0];
#pragma unroll
        for (int f = 1; f < 8; f++) {
            float4 q = make_float4(o[f].x * s0, o[f].y * s0, o[f].z * s1, o[f].w * s1);
            *reinterpret_cast<float4*>(&sm.S1[f * P1 + 2 * t]) = q;
        }
    }
    __syncthreads();
    {
        const int f = t / 40, n2 = t - f * 40;
        const float2* src = &sm.S1[f * P1 + n2];
#pragma unroll
        for (int n1 = 0; n1 < 16; n1++) v[n1] = src[40 * n1];
        dft16(v);
        float2* dst = &sm.S2[f * P2 + n2];
        dst[0] = v[0];
#pragma unroll
        for (int k1 = 1; k1 < 16; k1++) dst[41 * k1] = cmul(v[O16(k1)], sm.tw[(k1 - 1) * 40 + n2]);
    }
    __syncthreads();
    if (t < 128) {
        const int f = t >> 4, k1 = t & 15;
        float2 u[40];
        const float2* src = &sm.S2[f * P2 + 41 * k1];
#pragma unroll
        for (int n2 = 0; n2 < 40; n2++) u[n2] = src[n2];
        dft40(u);
        float2* baseA = g_I + ((size_t)(f * 80 + (k1 >> 3)) * 128 + g) * 8 + (k1 & 7);
        const int kk = (f == 0) ? ((k1 + 15) & 15) : k1;
        float2* baseB = g_I + ((size_t)(f * 80 + (kk >> 3)) * 128 + g) * 8 + (kk & 7);
        if (f == 0 && k1 == 0) baseB -= 2048;
        float2* p320 = (t == 0) ? (g_I + ((size_t)79 * 128 + g) * 8 + 7) : (baseB + 20 * 2048);
#pragma unroll
        for (int a = 0; a < 8; a++)
#pragma unroll
            for (int b = 0; b < 5; b++) {
                const int k2 = K40(a, b);
                float2 val = u[SL40(O8(a), b)];
                if (k2 < 20) baseA[k2 * 2048] = val;
                else if (k2 == 20) *p320 = val;
                else baseB[k2 * 2048] = val;
            }
    }
}

struct K2Smem {
    float2 E[5][16 * 72];
    float2 tw128[16 * 8];
    float2 tw256[128];
    float sc[640];
    float part[64 * 20];
};

__global__ void __launch_bounds__(320, 1)
k2_kernel(const bf16* __restrict__ wr, const bf16* __restrict__ wi, const bf16* __restrict__ c,
          const bf16* __restrict__ wmod, const bf16* __restrict__ w1, const bf16* __restrict__ w2) {
    extern __shared__ __align__(16) unsigned char smem_raw[];
    K2Smem& sm = *reinterpret_cast<K2Smem*>(smem_raw);
    const int t = threadIdx.x, lane = t & 31, slot = t >> 6;
    const int a = ((t >> 5) & 1) * 4 + (lane >> 3), col = lane & 7;
    const int task = slot * 129 + blockIdx.x;
    pdl_launch();

    int f, pos, q, kw;
    bool cpath = false, avg = false, odd = false, store;
    if (task < 80) {
        f = 0;
        odd = col >= 4;
        int k = 4 * task + (col & 3);
        pos = odd ? 639 - k : k;
        q = odd ? 8 : 0;
        kw = k;
        cpath = true;
        store = (k != 0);
    } else if (task < 640) {
        f = task / 80;
        int kb = task - f * 80;
        pos = kb * 8 + col;
        odd = kb >= 40;
        q = odd ? -f : f;
        kw = odd ? 640 - pos : pos;
        store = (pos != 0) && (pos != 320);
    } else if (task < 644) {
        int j = (task - 640) * 4 + (col & 3);
        odd = col >= 4;
        store = (j < 14) && !odd;
        if (j >= 14) j = 0;
        f = 1 + (j >> 1);
        pos = (j & 1) ? 320 : 0;
        q = odd ? -f : f;
        kw = pos;
        avg = true;
    } else {
        int j = col & 3;
        odd = col >= 4;
        store = (j < 2) && !odd;
        j &= 1;
        f = 0;
        pos = j ? 639 : 0;
        kw = j ? 320 : 0;
        q = odd ? 8 : 0;
        cpath = true;
        avg = true;
    }
    uint32_t wp[16];
#pragma unroll
    for (int i = 0; i < 2; i++)
#pragma unroll
        for (int cc = 0; cc < 8; cc++) {
            int ks = (q + 16 * (a + 8 * i) + 256 * cc) & 2047;
            int idx = ks * 321 + kw;
            wp[i * 8 + cc] = ldg_nc16(wr + idx) | (ldg_nc16(wi + idx) << 16);
        }
    if (t < 128) sm.tw128[t] = twiddle((t >> 3) * (t & 7), 2.0f / 128.0f);
    else if (t < 256) sm.tw256[t - 128] = twiddle(t - 128, 2.0f / 256.0f);
    if (blockIdx.x < 128) {
        const int j = t % 5, r0 = t / 5;
        uint2 wv[10];
#pragma unroll
        for (int i = 0; i < 10; i++)
            wv[i] = ldg_nc64(wmod + (size_t)(r0 + 64 * i) * 3840 + 1280 + 20 * blockIdx.x + 4 * j);
        {
            uint32_t cc = ldg_nc32(c + 2 * t);
            sm.sc[2 * t] = bf_round(silu_f(bf_lo(cc)));
            sm.sc[2 * t + 1] = bf_round(silu_f(bf_hi(cc)));
        }
        __syncthreads();
        float4 acc = make_float4(0.f, 0.f, 0.f, 0.f);
#pragma unroll
        for (int i = 0; i < 10; i++) {
            float s = sm.sc[r0 + 64 * i];
            acc.x = fmaf(s, bf_lo(wv[i].x), acc.x); acc.y = fmaf(s, bf_hi(wv[i].x), acc.y);
            acc.z = fmaf(s, bf_lo(wv[i].y), acc.z); acc.w = fmaf(s, bf_hi(wv[i].y), acc.w);
        }
        *reinterpret_cast<float4*>(&sm.part[r0 * 20 + 4 * j]) = acc;
        __syncthreads();
        if (t < 160) {
            const int cidx = t >> 3, seg = t & 7;
            float r = 0.f;
#pragma unroll
            for (int i = 0; i < 8; i++) r += sm.part[(seg + 8 * i) * 20 + cidx];
            r += __shfl_xor_sync(0xffffffffu, r, 1);
            r += __shfl_xor_sync(0xffffffffu, r, 2);
            r += __shfl_xor_sync(0xffffffffu, r, 4);
            float r2 = __shfl_down_sync(0xffffffffu, r, 8);
            if ((lane & 15) == 0) g_mod2[10 * blockIdx.x + (cidx >> 1)] = pack_bf2(r, r2);
        }
        if (t == 0) {
            const char* p1 = reinterpret_cast<const char*>(w1) + (size_t)blockIdx.x * 15360;
            const char* p2 = reinterpret_cast<const char*>(w2) + (size_t)blockIdx.x * 15360;
            asm volatile("cp.async.bulk.prefetch.L2.global [%0], %1;" ::"l"(p1), "r"(15360) : "memory");
            asm volatile("cp.async.bulk.prefetch.L2.global [%0], %1;" ::"l"(p2), "r"(15360) : "memory");
        }
    } else {
        __syncthreads();
    }

    pdl_wait();
    if (blockIdx.x == 128) {
        g_modw[t] = 0ull;
        g_modw[t + 320] = 0ull;
    }

    float2* ptr = g_I + ((size_t)(f * 80 + (pos >> 3)) * 128 + a) * 8 + (pos & 7);
    float2 v[16];
#pragma unroll
    for (int m = 0; m < 16; m++) v[m] = ldg_cg64(ptr + 64 * m);
    const float sgn = odd ? -1.0f : 1.0f;
    if (cpath) {
#pragma unroll
        for (int m = 0; m < 16; m++) {
            float2 z = v[m];
            float2 p = make_float2(__shfl_xor_sync(0xffffffffu, z.x, 4), __shfl_xor_sync(0xffffffffu, z.y, 4));
            float2 e = make_float2(z.x + p.x, z.y - p.y);
            float2 o = cmul(make_float2(p.y + z.y, z.x - p.x), sm.tw256[a + 8 * m]);
            v[m] = odd ? o : e;
        }
    } else {
#pragma unroll
        for (int m = 0; m < 16; m++) v[m].y *= sgn;
    }
    float2* E = sm.E[slot];
    dft16(v);
    E[a * 8 + col] = v[0];
#pragma unroll
    for (int b = 1; b < 16; b++) E[b * 72 + a * 8 + col] = cmul(v[O16(b)], sm.tw128[b * 8 + a]);
    asm volatile("bar.sync %0, 64;" ::"r"(slot + 1) : "memory");
#pragma unroll
    for (int i = 0; i < 2; i++) {
        float2* row = E + (a + 8 * i) * 72 + col;
        float2 u[8];
#pragma unroll
        for (int j = 0; j < 8; j++) u[j] = row[8 * j];
        dft8(u[0], u[1], u[2], u[3], u[4], u[5], u[6], u[7]);
        float2 y[8];
#pragma unroll
        for (int cc = 0; cc < 8; cc++) {
            float2 w = make_float2(bf_lo(wp[i * 8 + cc]), bf_hi(wp[i * 8 + cc]));
            float2 r = cmul(u[O8(cc)], w);
            y[cc] = make_float2(r.y, r.x);
        }
        dft8(y[0], y[1], y[2], y[3], y[4], y[5], y[6], y[7]);
        row[0] = y[0];
#pragma unroll
        for (int j = 1; j < 8; j++) row[8 * j] = cmul(y[O8(j)], sm.tw128[(a + 8 * i) * 8 + j]);
    }
    asm volatile("bar.sync %0, 64;" ::"r"(slot + 1) : "memory");
#pragma unroll
    for (int b = 0; b < 16; b++) v[b] = E[b * 72 + a * 8 + col];
    dft16(v);
    float2 r[16];
    if (cpath) {
#pragma unroll
        for (int m = 0; m < 16; m++) {
            float2 V = make_float2(v[O16(m)].y, v[O16(m)].x);
            float2 Vt = cmulc(V, sm.tw256[a + 8 * m]);
            V = odd ? Vt : V;
            float2 P = make_float2(__shfl_xor_sync(0xffffffffu, V.x, 4), __shfl_xor_sync(0xffffffffu, V.y, 4));
            r[m] = odd ? make_float2(P.x + V.y, V.x - P.y) : make_float2(V.x - P.y, V.y + P.x);
        }
    } else {
#pragma unroll
        for (int m = 0; m < 16; m++) r[m] = make_float2(v[O16(m)].y, sgn * v[O16(m)].x);
    }
    if (avg) {
#pragma unroll
        for (int m = 0; m < 16; m++) {
            r[m].x = 0.5f * (r[m].x + __shfl_xor_sync(0xffffffffu, r[m].x, 4));
            r[m].y = 0.5f * (r[m].y + __shfl_xor_sync(0xffffffffu, r[m].y, 4));
        }
    }
    if (store) {
#pragma unroll
        for (int m = 0; m < 16; m++) ptr[64 * m] = r[m];
    }
}

__device__ __forceinline__ void wgmma_n192_ss(float* d, uint64_t da, uint64_t db, int scale_d) {
    asm volatile("{\n.reg .pred p;\nsetp.ne.b32 p, %98, 0;\n"
        "wgmma.mma_async.sync.aligned.m64n192k16.f32.bf16.bf16 "
        "{%0, %1, %2, %3, %4, %5, %6, %7, %8, %9, %10, %11, %12, %13, %14, %15, "
        "%16, %17, %18, %19, %20, %21, %22, %23, %24, %25, %26, %27, %28, %29, %30, %31, "
        "%32, %33, %34, %35, %36, %37, %38, %39, %40, %41, %42, %43, %44, %45, %46, %47, "
        "%48, %49, %50, %51, %52, %53, %54, %55, %56, %57, %58, %59, %60, %61, %62, %63, "
        "%64, %65, %66, %67, %68, %69, %70, %71, %72, %73, %74, %75, %76, %77, %78, %79, "
        "%80, %81, %82, %83, %84, %85, %86, %87, %88, %89, %90, %91, %92, %93, %94, %95}, "
        "%96, %97, p, 1, 1, 0, 1;\n}\n"
        : "+f"(d[0]), "+f"(d[1]), "+f"(d[2]), "+f"(d[3]), "+f"(d[4]), "+f"(d[5]), "+f"(d[6]), "+f"(d[7]),
          "+f"(d[8]), "+f"(d[9]), "+f"(d[10]), "+f"(d[11]), "+f"(d[12]), "+f"(d[13]), "+f"(d[14]), "+f"(d[15]),
          "+f"(d[16]), "+f"(d[17]), "+f"(d[18]), "+f"(d[19]), "+f"(d[20]), "+f"(d[21]), "+f"(d[22]), "+f"(d[23]),
          "+f"(d[24]), "+f"(d[25]), "+f"(d[26]), "+f"(d[27]), "+f"(d[28]), "+f"(d[29]), "+f"(d[30]), "+f"(d[31]),
          "+f"(d[32]), "+f"(d[33]), "+f"(d[34]), "+f"(d[35]), "+f"(d[36]), "+f"(d[37]), "+f"(d[38]), "+f"(d[39]),
          "+f"(d[40]), "+f"(d[41]), "+f"(d[42]), "+f"(d[43]), "+f"(d[44]), "+f"(d[45]), "+f"(d[46]), "+f"(d[47]),
          "+f"(d[48]), "+f"(d[49]), "+f"(d[50]), "+f"(d[51]), "+f"(d[52]), "+f"(d[53]), "+f"(d[54]), "+f"(d[55]),
          "+f"(d[56]), "+f"(d[57]), "+f"(d[58]), "+f"(d[59]), "+f"(d[60]), "+f"(d[61]), "+f"(d[62]), "+f"(d[63]),
          "+f"(d[64]), "+f"(d[65]), "+f"(d[66]), "+f"(d[67]), "+f"(d[68]), "+f"(d[69]), "+f"(d[70]), "+f"(d[71]),
          "+f"(d[72]), "+f"(d[73]), "+f"(d[74]), "+f"(d[75]), "+f"(d[76]), "+f"(d[77]), "+f"(d[78]), "+f"(d[79]),
          "+f"(d[80]), "+f"(d[81]), "+f"(d[82]), "+f"(d[83]), "+f"(d[84]), "+f"(d[85]), "+f"(d[86]), "+f"(d[87]),
          "+f"(d[88]), "+f"(d[89]), "+f"(d[90]), "+f"(d[91]), "+f"(d[92]), "+f"(d[93]), "+f"(d[94]), "+f"(d[95])
        : "l"(da), "l"(db), "r"(scale_d));
}
__device__ __forceinline__ void wgmma_n192_rs(float* d, const uint32_t* a, uint64_t db, int scale_d) {
    asm volatile("{\n.reg .pred p;\nsetp.ne.b32 p, %101, 0;\n"
        "wgmma.mma_async.sync.aligned.m64n192k16.f32.bf16.bf16 "
        "{%0, %1, %2, %3, %4, %5, %6, %7, %8, %9, %10, %11, %12, %13, %14, %15, "
        "%16, %17, %18, %19, %20, %21, %22, %23, %24, %25, %26, %27, %28, %29, %30, %31, "
        "%32, %33, %34, %35, %36, %37, %38, %39, %40, %41, %42, %43, %44, %45, %46, %47, "
        "%48, %49, %50, %51, %52, %53, %54, %55, %56, %57, %58, %59, %60, %61, %62, %63, "
        "%64, %65, %66, %67, %68, %69, %70, %71, %72, %73, %74, %75, %76, %77, %78, %79, "
        "%80, %81, %82, %83, %84, %85, %86, %87, %88, %89, %90, %91, %92, %93, %94, %95}, "
        "{%96, %97, %98, %99}, %100, p, 1, 1, 1;\n}\n"
        : "+f"(d[0]), "+f"(d[1]), "+f"(d[2]), "+f"(d[3]), "+f"(d[4]), "+f"(d[5]), "+f"(d[6]), "+f"(d[7]),
          "+f"(d[8]), "+f"(d[9]), "+f"(d[10]), "+f"(d[11]), "+f"(d[12]), "+f"(d[13]), "+f"(d[14]), "+f"(d[15]),
          "+f"(d[16]), "+f"(d[17]), "+f"(d[18]), "+f"(d[19]), "+f"(d[20]), "+f"(d[21]), "+f"(d[22]), "+f"(d[23]),
          "+f"(d[24]), "+f"(d[25]), "+f"(d[26]), "+f"(d[27]), "+f"(d[28]), "+f"(d[29]), "+f"(d[30]), "+f"(d[31]),
          "+f"(d[32]), "+f"(d[33]), "+f"(d[34]), "+f"(d[35]), "+f"(d[36]), "+f"(d[37]), "+f"(d[38]), "+f"(d[39]),
          "+f"(d[40]), "+f"(d[41]), "+f"(d[42]), "+f"(d[43]), "+f"(d[44]), "+f"(d[45]), "+f"(d[46]), "+f"(d[47]),
          "+f"(d[48]), "+f"(d[49]), "+f"(d[50]), "+f"(d[51]), "+f"(d[52]), "+f"(d[53]), "+f"(d[54]), "+f"(d[55]),
          "+f"(d[56]), "+f"(d[57]), "+f"(d[58]), "+f"(d[59]), "+f"(d[60]), "+f"(d[61]), "+f"(d[62]), "+f"(d[63]),
          "+f"(d[64]), "+f"(d[65]), "+f"(d[66]), "+f"(d[67]), "+f"(d[68]), "+f"(d[69]), "+f"(d[70]), "+f"(d[71]),
          "+f"(d[72]), "+f"(d[73]), "+f"(d[74]), "+f"(d[75]), "+f"(d[76]), "+f"(d[77]), "+f"(d[78]), "+f"(d[79]),
          "+f"(d[80]), "+f"(d[81]), "+f"(d[82]), "+f"(d[83]), "+f"(d[84]), "+f"(d[85]), "+f"(d[86]), "+f"(d[87]),
          "+f"(d[88]), "+f"(d[89]), "+f"(d[90]), "+f"(d[91]), "+f"(d[92]), "+f"(d[93]), "+f"(d[94]), "+f"(d[95])
        : "r"(a[0]), "r"(a[1]), "r"(a[2]), "r"(a[3]), "l"(db), "r"(scale_d));
}
__device__ __forceinline__ void wgmma_n128_rs(float* d, const uint32_t* a, uint64_t db, int scale_d) {
    asm volatile("{\n.reg .pred p;\nsetp.ne.b32 p, %69, 0;\n"
        "wgmma.mma_async.sync.aligned.m64n128k16.f32.bf16.bf16 "
        "{%0, %1, %2, %3, %4, %5, %6, %7, %8, %9, %10, %11, %12, %13, %14, %15, "
        "%16, %17, %18, %19, %20, %21, %22, %23, %24, %25, %26, %27, %28, %29, %30, %31, "
        "%32, %33, %34, %35, %36, %37, %38, %39, %40, %41, %42, %43, %44, %45, %46, %47, "
        "%48, %49, %50, %51, %52, %53, %54, %55, %56, %57, %58, %59, %60, %61, %62, %63}, "
        "{%64, %65, %66, %67}, %68, p, 1, 1, 1;\n}\n"
        : "+f"(d[0]), "+f"(d[1]), "+f"(d[2]), "+f"(d[3]), "+f"(d[4]), "+f"(d[5]), "+f"(d[6]), "+f"(d[7]),
          "+f"(d[8]), "+f"(d[9]), "+f"(d[10]), "+f"(d[11]), "+f"(d[12]), "+f"(d[13]), "+f"(d[14]), "+f"(d[15]),
          "+f"(d[16]), "+f"(d[17]), "+f"(d[18]), "+f"(d[19]), "+f"(d[20]), "+f"(d[21]), "+f"(d[22]), "+f"(d[23]),
          "+f"(d[24]), "+f"(d[25]), "+f"(d[26]), "+f"(d[27]), "+f"(d[28]), "+f"(d[29]), "+f"(d[30]), "+f"(d[31]),
          "+f"(d[32]), "+f"(d[33]), "+f"(d[34]), "+f"(d[35]), "+f"(d[36]), "+f"(d[37]), "+f"(d[38]), "+f"(d[39]),
          "+f"(d[40]), "+f"(d[41]), "+f"(d[42]), "+f"(d[43]), "+f"(d[44]), "+f"(d[45]), "+f"(d[46]), "+f"(d[47]),
          "+f"(d[48]), "+f"(d[49]), "+f"(d[50]), "+f"(d[51]), "+f"(d[52]), "+f"(d[53]), "+f"(d[54]), "+f"(d[55]),
          "+f"(d[56]), "+f"(d[57]), "+f"(d[58]), "+f"(d[59]), "+f"(d[60]), "+f"(d[61]), "+f"(d[62]), "+f"(d[63])
        : "r"(a[0]), "r"(a[1]), "r"(a[2]), "r"(a[3]), "l"(db), "r"(scale_d));
}
__device__ __forceinline__ void wgmma_n64_rs(float* d, const uint32_t* a, uint64_t db, int scale_d) {
    asm volatile("{\n.reg .pred p;\nsetp.ne.b32 p, %37, 0;\n"
        "wgmma.mma_async.sync.aligned.m64n64k16.f32.bf16.bf16 "
        "{%0, %1, %2, %3, %4, %5, %6, %7, %8, %9, %10, %11, %12, %13, %14, %15, "
        "%16, %17, %18, %19, %20, %21, %22, %23, %24, %25, %26, %27, %28, %29, %30, %31}, "
        "{%32, %33, %34, %35}, %36, p, 1, 1, 1;\n}\n"
        : "+f"(d[0]), "+f"(d[1]), "+f"(d[2]), "+f"(d[3]), "+f"(d[4]), "+f"(d[5]), "+f"(d[6]), "+f"(d[7]),
          "+f"(d[8]), "+f"(d[9]), "+f"(d[10]), "+f"(d[11]), "+f"(d[12]), "+f"(d[13]), "+f"(d[14]), "+f"(d[15]),
          "+f"(d[16]), "+f"(d[17]), "+f"(d[18]), "+f"(d[19]), "+f"(d[20]), "+f"(d[21]), "+f"(d[22]), "+f"(d[23]),
          "+f"(d[24]), "+f"(d[25]), "+f"(d[26]), "+f"(d[27]), "+f"(d[28]), "+f"(d[29]), "+f"(d[30]), "+f"(d[31])
        : "r"(a[0]), "r"(a[1]), "r"(a[2]), "r"(a[3]), "l"(db), "r"(scale_d));
}

__device__ __forceinline__ void wg_fence() { asm volatile("wgmma.fence.sync.aligned;" ::: "memory"); }
__device__ __forceinline__ void wg_commit() { asm volatile("wgmma.commit_group.sync.aligned;" ::: "memory"); }
template <int N>
__device__ __forceinline__ void wg_wait() { asm volatile("wgmma.wait_group.sync.aligned %0;" ::"n"(N) : "memory"); }

__device__ __forceinline__ uint32_t smem_u32(const void* p) { return (uint32_t)__cvta_generic_to_shared(p); }
__device__ __forceinline__ uint32_t mapa(uint32_t addr, uint32_t rank) {
    uint32_t r;
    asm("mapa.shared::cluster.u32 %0, %1, %2;" : "=r"(r) : "r"(addr), "r"(rank));
    return r;
}
__device__ __forceinline__ void mbar_init(uint32_t bar, uint32_t count) {
    asm volatile("mbarrier.init.shared::cta.b64 [%0], %1;" ::"r"(bar), "r"(count) : "memory");
}
__device__ __forceinline__ void mbar_arrive(uint32_t bar) {
    asm volatile("mbarrier.arrive.shared::cta.b64 _, [%0];" ::"r"(bar) : "memory");
}
__device__ __forceinline__ void mbar_arrive_remote(uint32_t cluster_bar) {
    asm volatile("mbarrier.arrive.release.cluster.shared::cluster.b64 _, [%0];" ::"r"(cluster_bar) : "memory");
}
__device__ __forceinline__ void mbar_expect_tx(uint32_t bar, uint32_t bytes) {
    asm volatile("mbarrier.arrive.expect_tx.shared::cta.b64 _, [%0], %1;" ::"r"(bar), "r"(bytes) : "memory");
}
__device__ __forceinline__ void mbar_wait(uint32_t bar, uint32_t parity) {
    uint32_t ok;
    int it = 0;
    do {
        asm volatile(
            "{\n.reg .pred p;\n"
            "mbarrier.try_wait.parity.acquire.cluster.shared::cta.b64 p, [%1], %2;\n"
            "selp.u32 %0, 1, 0, p;\n}\n"
            : "=r"(ok) : "r"(bar), "r"(parity) : "memory");
    } while (!ok && ++it < (1 << 16));
}
__device__ __forceinline__ void tma_load3(uint32_t dst, const CUtensorMap* tm, int c1, int c2, uint32_t bar) {
    asm volatile(
        "cp.async.bulk.tensor.3d.shared::cluster.global.mbarrier::complete_tx::bytes [%0], [%1, {%2, %3, %4}], [%5];"
        ::"r"(dst), "l"(tm), "r"(0), "r"(c1), "r"(c2), "r"(bar) : "memory");
}
__device__ __forceinline__ void fence_async() { asm volatile("fence.proxy.async.shared::cta;" ::: "memory"); }
__device__ __forceinline__ uint64_t make_desc(uint32_t addr, uint32_t lbo, uint32_t sbo) {
    return (uint64_t)((addr & 0x3FFFF) >> 4) | ((uint64_t)(lbo >> 4) << 16) | ((uint64_t)(sbo >> 4) << 32) |
           (1ull << 62);
}
__device__ __forceinline__ float ex2f(float v) { float r; asm("ex2.approx.ftz.f32 %0, %1;" : "=f"(r) : "f"(v)); return r; }
__device__ __forceinline__ float rcpf(float v) { float r; asm("rcp.approx.ftz.f32 %0, %1;" : "=f"(r) : "f"(v)); return r; }
__device__ __forceinline__ void silu4(const float* d, uint32_t& o0, uint32_t& o1) {
    uint32_t p0 = pack_bf2(d[0], d[1]), p1 = pack_bf2(d[2], d[3]);
    float v0 = fmaxf(bf_lo(p0), -20.f), v1 = fmaxf(bf_hi(p0), -20.f);
    float v2 = fmaxf(bf_lo(p1), -20.f), v3 = fmaxf(bf_hi(p1), -20.f);
    const float nl = -1.4426950408889634f;
    float a0 = 1.f + ex2f(v0 * nl), a1 = 1.f + ex2f(v1 * nl), a2 = 1.f + ex2f(v2 * nl), a3 = 1.f + ex2f(v3 * nl);
    float p01 = a0 * a1, p23 = a2 * a3;
    float r = rcpf(p01 * p23);
    float r01 = r * p23, r23 = r * p01;
    o0 = pack_bf2(v0 * (r01 * a1), v1 * (r01 * a0));
    o1 = pack_bf2(v2 * (r23 * a3), v3 * (r23 * a2));
}

#define K3_H2 0
#define K3_TW 43008
#define K3_RING 163840
#define K3_SLOT 12288
#define K3_MISC 225280
#define K3_SMEM (K3_MISC + 2048 + 1024)
#define BAR_FULL 0
#define BAR_EMPTY 40
#define BAR_H2 80
#define BAR_R 160
#define BAR_FREE 200
#define BAR_G1 208
#define MISC_T 256
#define MISC_RED 384

__device__ __forceinline__ void k3_issue(int it, uint32_t ring, uint32_t misc, int j, const CUtensorMap* tw1,
                                         const CUtensorMap* tw2a, const CUtensorMap* tw2b, const CUtensorMap* tw2c) {
    const int slot = it % 5;
    const uint32_t bar = misc + BAR_FULL + 8 * slot, dst = ring + slot * K3_SLOT;
    mbar_expect_tx(bar, K3_SLOT);
    if (it < 20) tma_load3(dst, tw1, 32 * it, 3 * j, bar);
    else if (it < 24) tma_load3(dst, tw2b, 192 * j + 48 * (it - 20), 0, bar);
    else if (it < 30) tma_load3(dst, tw2a, 192 * j + 32 * (it - 24), 2, bar);
    else if (it < 38) tma_load3(dst, tw2b, 192 * j + 48 * ((it - 30) & 3), 5 + 2 * ((it - 30) >> 2), bar);
    else tma_load3(dst, tw2c, 192 * j + 96 * (it - 38), 9, bar);
}

template <int NU>
__device__ __forceinline__ void k3_send(const float* acc, uint32_t rdst, uint32_t rbar, int u0) {
#pragma unroll
    for (int u = 0; u < NU; u++) {
        uint32_t w0 = pack_bf2(acc[8 * u + 0], acc[8 * u + 1]), w1 = pack_bf2(acc[8 * u + 2], acc[8 * u + 3]);
        uint32_t w2 = pack_bf2(acc[8 * u + 4], acc[8 * u + 5]), w3 = pack_bf2(acc[8 * u + 6], acc[8 * u + 7]);
        asm volatile("st.async.weak.shared::cluster.mbarrier::complete_tx::bytes.v4.b32 [%0], {%1,%2,%3,%4}, [%5];"
                     ::"r"(rdst + (u0 + u) * 512), "r"(w0), "r"(w1), "r"(w2), "r"(w3), "r"(rbar) : "memory");
    }
}

__global__ void __cluster_dims__(8, 1, 1) __launch_bounds__(384, 1)
k3_kernel(const bf16* __restrict__ x, bf16* __restrict__ out, const __grid_constant__ CUtensorMap tw1,
          const __grid_constant__ CUtensorMap tw2a, const __grid_constant__ CUtensorMap tw2b,
          const __grid_constant__ CUtensorMap tw2c) {
    extern __shared__ __align__(16) unsigned char smem_raw[];
    const uint32_t sbase = (smem_u32(smem_raw) + 1023u) & ~1023u;
    unsigned char* sptr = smem_raw + (sbase - smem_u32(smem_raw));
    const uint32_t misc = sbase + K3_MISC, ring = sbase + K3_RING;
    float2* S2 = reinterpret_cast<float2*>(sptr);
    float2* stw = reinterpret_cast<float2*>(sptr + K3_TW);
    float2* sT = reinterpret_cast<float2*>(sptr + K3_MISC + MISC_T);
    float* red = reinterpret_cast<float*>(sptr + K3_MISC + MISC_RED);
    const int t = threadIdx.x, g = blockIdx.x, lane = t & 31, warp = t >> 5;
    const int j = g & 7;

    uint32_t xr[16];
    if (warp == 11) {
        if (lane == 0) {
#pragma unroll
            for (int i = 0; i < 5; i++) { mbar_init(misc + BAR_FULL + 8 * i, 1); mbar_init(misc + BAR_EMPTY + 8 * i, 8); }
#pragma unroll
            for (int i = 0; i < 10; i++) mbar_init(misc + BAR_H2 + 8 * i, 1);
#pragma unroll
            for (int i = 0; i < 5; i++) mbar_init(misc + BAR_R + 8 * i, 1);
            mbar_init(misc + BAR_FREE, 8);
            mbar_init(misc + BAR_G1, 64);
            asm volatile("fence.mbarrier_init.release.cluster;" ::: "memory");
            mbar_expect_tx(misc + BAR_R + 0, 8 * 4096);
            mbar_expect_tx(misc + BAR_R + 8, 12 * 4096);
            mbar_expect_tx(misc + BAR_R + 16, 8 * 4096);
            mbar_expect_tx(misc + BAR_R + 24, 8 * 4096);
            mbar_expect_tx(misc + BAR_R + 32, 4 * 4096);
#pragma unroll
            for (int it = 0; it < 5; it++) k3_issue(it, ring, misc, j, &tw1, &tw2a, &tw2b, &tw2c);
        }
    } else if (warp < 10) {
#pragma unroll
        for (int m = 0; m < 16; m++) xr[m] = ldg_nc32(x + (size_t)(g + 128 * m) * 640 + 2 * t);
        int i = t;
        stw[i] = twiddle((i % 40) * (i / 40 + 1), 2.0f / 640.0f);
        i = t + 320;
        if (i < 600) stw[i] = twiddle((i % 40) * (i / 40 + 1), 2.0f / 640.0f);
    } else if (lane < 8) {
        float2 T = twiddle(g * lane, 2.0f / 2048.0f);
        const float nrm = 1.0f / (2048.0f * 640.0f);
        sT[lane] = make_float2(T.x * nrm, T.y * nrm);
    }
    asm volatile("barrier.cluster.arrive.release.aligned;" ::: "memory");
    asm volatile("barrier.cluster.wait.acquire.aligned;" ::: "memory");
    pdl_wait();

    if (warp < 10) {
        float2 v[16];
        {
            const int f = t / 40, b = t - f * 40;
            const float2* baseA = g_I + ((size_t)(f * 80 + (b >> 3)) * 128 + g) * 8 + (b & 7);
            const int bb = (f == 0) ? (b == 0 ? 39 : b - 1) : b;
            const float2* baseB = g_I + ((size_t)(f * 80 + (bb >> 3)) * 128 + g) * 8 + (bb & 7);
            if (t == 0) baseB -= 5 * 1024;
            const float2* p320 = (t == 0) ? (g_I + ((size_t)79 * 128 + g) * 8 + 7) : (baseB + 8 * 5 * 1024);
#pragma unroll
            for (int a = 0; a < 16; a++) {
                float2 z = ldg_cg64(a < 8 ? baseA + a * 5 * 1024 : (a == 8 ? p320 : baseB + a * 5 * 1024));
                v[a] = make_float2(z.y, z.x);
            }
            dft16(v);
            float2* dst = &S2[f * P2 + b];
            dst[0] = v[0];
#pragma unroll
            for (int k1 = 1; k1 < 16; k1++) dst[41 * k1] = cmul(v[O16(k1)], stw[(k1 - 1) * 40 + b]);
        }
        const uint32_t ga2 = __ldcg(&g_mod2[t]), sb2 = __ldcg(&g_mod2[320 + t]), cb2 = __ldcg(&g_mod2[640 + t]);
        asm volatile("bar.sync 1, 320;" ::: "memory");
        if (t < 128) {
            const int f = t >> 4, n1 = t & 15;
            float2 u[40];
            const float2* src = &S2[f * P2 + 41 * n1];
#pragma unroll
            for (int n2 = 0; n2 < 40; n2++) u[n2] = src[n2];
            dft40(u);
            __syncwarp();
            float2* dst = &S2[f * P2 + n1];
#pragma unroll
            for (int a = 0; a < 8; a++)
#pragma unroll
                for (int b = 0; b < 5; b++) dst[16 * K40(a, b)] = u[SL40(O8(a), b)];
        }
        asm volatile("bar.sync 1, 320;" ::: "memory");
        {
            float4 z0 = *reinterpret_cast<const float4*>(&S2[2 * t]);
            const float nrm = sT[0].x;
            v[0] = make_float2(z0.w * nrm, z0.y * nrm);
            v[8] = make_float2(z0.z * nrm, z0.x * nrm);
#pragma unroll
            for (int f = 1; f < 8; f++) {
                float4 z = *reinterpret_cast<const float4*>(&S2[f * P2 + 2 * t]);
                float2 T = sT[f];
                float2 A0 = cmulc(make_float2(z.y, z.x), T);
                float2 A1 = cmulc(make_float2(z.w, z.z), T);
                v[f] = make_float2(A0.y + A1.x, A0.x - A1.y);
                v[16 - f] = make_float2(A1.x - A0.y, A0.x + A1.y);
            }
            dft16(v);
        }
        float s[16];
#pragma unroll
        for (int m = 0; m < 16; m++) {
            uint32_t y2 = pack_bf2(v[O16(m)].y, v[O16(m)].x);
            __nv_bfloat162 p = __hmul2(*reinterpret_cast<const __nv_bfloat162*>(&ga2), *reinterpret_cast<__nv_bfloat162*>(&y2));
            __nv_bfloat162 r = __hadd2(*reinterpret_cast<__nv_bfloat162*>(&xr[m]), p);
            xr[m] = *reinterpret_cast<uint32_t*>(&r);
            s[m] = bf_lo(xr[m]) + bf_hi(xr[m]);
            *reinterpret_cast<uint32_t*>(out + (size_t)(g + 128 * m) * 640 + 2 * t) = xr[m];
        }
        {
            float r = warp_reduce16(s, lane);
            if (!(lane & 1)) red[warp * 16 + (lane >> 1)] = r;
        }
        fence_async();
        asm volatile("bar.sync 1, 320;" ::: "memory");
        if (t < 8) mbar_arrive_remote(mapa(misc + BAR_FREE, t));
        float mean_l;
        {
            float r = 0.f;
#pragma unroll
            for (int i = 0; i < 5; i++) r += red[((lane & 1) * 5 + i) * 16 + (lane >> 1)];
            r += __shfl_xor_sync(0xffffffffu, r, 1);
            mean_l = r * (1.0f / 640.0f);
        }
#pragma unroll
        for (int m = 0; m < 16; m++) {
            float mu = __shfl_sync(0xffffffffu, mean_l, 2 * m);
            float a = bf_lo(xr[m]) - mu, b = bf_hi(xr[m]) - mu;
            s[m] = a * a + b * b;
        }
        {
            float r = warp_reduce16(s, lane);
            if (!(lane & 1)) red[160 + warp * 16 + (lane >> 1)] = r;
        }
        asm volatile("bar.sync 1, 320;" ::: "memory");
        {
            float r = 0.f;
#pragma unroll
            for (int i = 0; i < 5; i++) r += red[160 + ((lane & 1) * 5 + i) * 16 + (lane >> 1)];
            r += __shfl_xor_sync(0xffffffffu, r, 1);
            float var = bf_round(r * (1.0f / 640.0f));
            float den = bf_round(sqrtf(bf_round(var + 1e-5f)));
            float rs = 1.0f / den;
            float mr = bf_round(mean_l) * rs;
            const float c0 = bf_round(1.0f + bf_lo(cb2)), c1 = bf_round(1.0f + bf_hi(cb2));
            const float b0 = bf_lo(sb2), b1 = bf_hi(sb2);
            unsigned char* piece = sptr + K3_H2 + warp * 16384 + j * 2048 + (lane & 3) * 4;
#pragma unroll
            for (int m = 0; m < 16; m++) {
                float rr = __shfl_sync(0xffffffffu, rs, 2 * m);
                float mm = __shfl_sync(0xffffffffu, mr, 2 * m);
                float h0 = fmaf(fmaf(bf_lo(xr[m]), rr, -mm), c0, b0);
                float h1 = fmaf(fmaf(bf_hi(xr[m]), rr, -mm), c1, b1);
                *reinterpret_cast<uint32_t*>(piece + m * 128 + (((lane >> 2) ^ (m & 7)) << 4)) = pack_bf2(h0, h1);
            }
        }
        fence_async();
        __syncwarp();
        if (lane < 8) {
            const uint32_t hb = misc + BAR_H2 + 8 * warp;
            if (lane == j) {
                mbar_expect_tx(hb, 7 * 2048);
            } else {
                mbar_wait(misc + BAR_FREE, 0);
                const uint32_t src = sbase + K3_H2 + warp * 16384 + j * 2048;
                asm volatile(
                    "cp.async.bulk.shared::cluster.shared::cta.mbarrier::complete_tx::bytes [%0], [%1], %2, [%3];"
                    ::"r"(mapa(src, lane)), "r"(src), "r"(2048), "r"(mapa(hb, lane)) : "memory");
            }
        }
        __syncwarp();
    }

    if (warp < 8) {
        asm volatile("setmaxnreg.inc.sync.aligned.u32 208;");
        const int wg = warp >> 2;
        float acc[96];
        int slot = 0;
        uint32_t ph = 0;
        const uint64_t dA0 = make_desc(sbase + K3_H2 + wg * 8192, 16, 1024);
        const uint64_t dB32 = make_desc(ring, 4096, 1024);
        int prev = -1;
#pragma unroll 1
        for (int kc = 0; kc < 10; kc++) {
            mbar_wait(misc + BAR_H2 + 8 * kc, 0);
#pragma unroll
            for (int h = 0; h < 2; h++) {
                mbar_wait(misc + BAR_FULL + 8 * slot, ph);
                wg_fence();
                const uint64_t da = dA0 + (uint64_t)(kc * 1024 + h * 4);
                const uint64_t db = dB32 + (uint64_t)(slot * (K3_SLOT >> 4));
                wgmma_n192_ss(acc, da, db, (kc | h) != 0);
                wgmma_n192_ss(acc, da + 2, db + 128, 1);
                wg_commit();
                wg_wait<1>();
                if (prev >= 0 && lane == 0) mbar_arrive(misc + BAR_EMPTY + 8 * prev);
                prev = slot;
                if (++slot == 5) { slot = 0; ph ^= 1; }
            }
        }
        wg_wait<0>();
        if (lane == 0) mbar_arrive(misc + BAR_EMPTY + 8 * prev);
        if (lane < 8) mbar_arrive_remote(mapa(misc + BAR_G1, lane));
        prev = -1;

        const uint32_t rdst = mapa(sbase + K3_H2 + j * (40 * 512) + lane * 16, warp);
        const uint32_t rbar = mapa(misc + BAR_R, warp);
        uint32_t a[48];
        float acc2[96];
        const uint64_t dB48 = make_desc(ring, 6144, 1024);
#pragma unroll
        for (int s = 0; s < 4; s++) {
            mbar_wait(misc + BAR_FULL + 8 * slot, ph);
            const uint64_t db = dB48 + (uint64_t)(slot * (K3_SLOT >> 4));
#pragma unroll
            for (int ks = 0; ks < 3; ks++) {
                const int jj = 3 * s + ks;
                silu4(acc + 8 * jj, a[4 * jj], a[4 * jj + 1]);
                silu4(acc + 8 * jj + 4, a[4 * jj + 2], a[4 * jj + 3]);
                wg_fence();
                wgmma_n128_rs(acc2, a + 4 * jj, db + 128 * ks, jj != 0);
                wg_commit();
                if (ks == 0 && s > 0) {
                    wg_wait<1>();
                    if (lane == 0) mbar_arrive(misc + BAR_EMPTY + 8 * prev);
                }
            }
            prev = slot;
            if (++slot == 5) { slot = 0; ph ^= 1; }
        }
        wg_wait<0>();
        if (lane == 0) mbar_arrive(misc + BAR_EMPTY + 8 * prev);
        mbar_wait(misc + BAR_G1, 0);
        k3_send<8>(acc2, rdst, rbar, 0);
#pragma unroll
        for (int s = 0; s < 6; s++) {
            mbar_wait(misc + BAR_FULL + 8 * slot, ph);
            const uint64_t db = dB32 + (uint64_t)(slot * (K3_SLOT >> 4));
            wg_fence();
#pragma unroll
            for (int ks = 0; ks < 2; ks++) wgmma_n192_rs(acc2, a + 4 * (2 * s + ks), db + 128 * ks, (s | ks) != 0);
            wg_commit();
            if (s > 0) {
                wg_wait<1>();
                if (lane == 0) mbar_arrive(misc + BAR_EMPTY + 8 * prev);
            }
            prev = slot;
            if (++slot == 5) { slot = 0; ph ^= 1; }
        }
        wg_wait<0>();
        if (lane == 0) mbar_arrive(misc + BAR_EMPTY + 8 * prev);
        k3_send<12>(acc2, rdst, rbar + 8, 8);
#pragma unroll 1
        for (int c = 2; c < 4; c++) {
#pragma unroll
            for (int s = 0; s < 4; s++) {
                mbar_wait(misc + BAR_FULL + 8 * slot, ph);
                const uint64_t db = dB48 + (uint64_t)(slot * (K3_SLOT >> 4));
                wg_fence();
#pragma unroll
                for (int ks = 0; ks < 3; ks++) wgmma_n128_rs(acc2, a + 4 * (3 * s + ks), db + 128 * ks, (s | ks) != 0);
                wg_commit();
                if (s > 0) {
                    wg_wait<1>();
                    if (lane == 0) mbar_arrive(misc + BAR_EMPTY + 8 * prev);
                }
                prev = slot;
                if (++slot == 5) { slot = 0; ph ^= 1; }
            }
            wg_wait<0>();
            if (lane == 0) mbar_arrive(misc + BAR_EMPTY + 8 * prev);
            k3_send<8>(acc2, rdst, rbar + 8 * c, 4 + 8 * c);
        }
#pragma unroll
        for (int s = 0; s < 2; s++) {
            mbar_wait(misc + BAR_FULL + 8 * slot, ph);
            const uint64_t db = dB48 + (uint64_t)(slot * (K3_SLOT >> 4));
            wg_fence();
#pragma unroll
            for (int ks = 0; ks < 6; ks++) wgmma_n64_rs(acc2, a + 4 * (6 * s + ks), db + 128 * ks, (s | ks) != 0);
            wg_commit();
            if (++slot == 5) { slot = 0; ph ^= 1; }
        }
        wg_wait<0>();
        k3_send<4>(acc2, rdst, rbar + 32, 36);
    } else {
        asm volatile("setmaxnreg.dec.sync.aligned.u32 88;");
        const int rw = warp - 8;
        if (rw == 3) {
            if (lane == 0) {
#pragma unroll 1
                for (int it = 5; it < 40; it++) {
                    mbar_wait(misc + BAR_EMPTY + 8 * (it % 5), ((it / 5) - 1) & 1);
                    k3_issue(it, ring, misc, j, &tw1, &tw2a, &tw2b, &tw2c);
                }
            }
            __syncwarp();
        }
#pragma unroll 1
        for (int kc = 0; kc < 10; kc++) mbar_wait(misc + BAR_H2 + 8 * kc, 0);
        const int r = lane >> 2, q = lane & 3;
        bf16* orow0 = out + (size_t)(g + 128 * r) * 640 + 2 * q;
        bf16* orow1 = orow0 + (size_t)128 * 8 * 640;
        const unsigned char* R = sptr + K3_H2 + lane * 16;
#pragma unroll 1
        for (int u = (rw == 3) ? 39 : rw; u < 40; u += (u + 3 < 36) ? 3 : (u < 36 ? 36 + rw - u : 40)) {
            uint32_t xw[4], gb[2];
            xw[0] = __ldcg(reinterpret_cast<const uint32_t*>(orow0 + 16 * u));
            xw[1] = __ldcg(reinterpret_cast<const uint32_t*>(orow1 + 16 * u));
            xw[2] = __ldcg(reinterpret_cast<const uint32_t*>(orow0 + 16 * u + 8));
            xw[3] = __ldcg(reinterpret_cast<const uint32_t*>(orow1 + 16 * u + 8));
            gb[0] = __ldcg(&g_mod2[960 + 8 * u + q]);
            gb[1] = __ldcg(&g_mod2[960 + 8 * u + 4 + q]);
            const int c = u < 8 ? 0 : (u < 20 ? 1 : ((u - 4) >> 3));
            mbar_wait(misc + BAR_R + 8 * c, 0);
            float sum[8];
#pragma unroll
            for (int i = 0; i < 8; i++) sum[i] = 0.f;
#pragma unroll
            for (int src = 0; src < 8; src++) {
                uint4 w = *reinterpret_cast<const uint4*>(R + (src * 40 + u) * 512);
                sum[0] += bf_lo(w.x); sum[1] += bf_hi(w.x);
                sum[2] += bf_lo(w.y); sum[3] += bf_hi(w.y);
                sum[4] += bf_lo(w.z); sum[5] += bf_hi(w.z);
                sum[6] += bf_lo(w.w); sum[7] += bf_hi(w.w);
            }
            uint32_t o[4];
#pragma unroll
            for (int i = 0; i < 4; i++) {
                uint32_t f2 = pack_bf2(sum[2 * i], sum[2 * i + 1]);
                __nv_bfloat162 p = __hmul2(*reinterpret_cast<const __nv_bfloat162*>(&gb[i >> 1]), *reinterpret_cast<__nv_bfloat162*>(&f2));
                __nv_bfloat162 rr = __hadd2(*reinterpret_cast<__nv_bfloat162*>(&xw[i]), p);
                o[i] = *reinterpret_cast<uint32_t*>(&rr);
            }
            *reinterpret_cast<uint32_t*>(orow0 + 16 * u) = o[0];
            *reinterpret_cast<uint32_t*>(orow1 + 16 * u) = o[1];
            *reinterpret_cast<uint32_t*>(orow0 + 16 * u + 8) = o[2];
            *reinterpret_cast<uint32_t*>(orow1 + 16 * u + 8) = o[3];
        }
    }
}

template <typename... KArgs, typename... Args>
static void launch_pdl(void (*kern)(KArgs...), dim3 grid, dim3 block, size_t smem, bool pdl, Args... args) {
    cudaLaunchConfig_t cfg = {};
    cfg.gridDim = grid;
    cfg.blockDim = block;
    cfg.dynamicSmemBytes = smem;
    cfg.stream = cudaStreamPerThread;
    cudaLaunchAttribute at[1];
    at[0].id = cudaLaunchAttributeProgrammaticStreamSerialization;
    at[0].val.programmaticStreamSerializationAllowed = 1;
    cfg.attrs = at;
    cfg.numAttrs = pdl ? 1 : 0;
    cudaLaunchKernelEx(&cfg, kern, KArgs(args)...);
}

typedef CUresult (*EncodeFn)(CUtensorMap*, CUtensorMapDataType, cuuint32_t, void*, const cuuint64_t*, const cuuint64_t*,
                             const cuuint32_t*, const cuuint32_t*, CUtensorMapInterleave, CUtensorMapSwizzle,
                             CUtensorMapL2promotion, CUtensorMapFloatOOBfill);

static void make_map(EncodeFn enc, CUtensorMap* m, const void* base, int rows, int cols, int box_rows, int box_blks) {
    cuuint64_t dims[3] = {64, (cuuint64_t)rows, (cuuint64_t)(cols / 64)};
    cuuint64_t strides[2] = {(cuuint64_t)cols * 2, 128};
    cuuint32_t box[3] = {64, (cuuint32_t)box_rows, (cuuint32_t)box_blks};
    cuuint32_t es[3] = {1, 1, 1};
    enc(m, CU_TENSOR_MAP_DATA_TYPE_BFLOAT16, 3, const_cast<void*>(base), dims, strides, box, es,
        CU_TENSOR_MAP_INTERLEAVE_NONE, CU_TENSOR_MAP_SWIZZLE_128B, CU_TENSOR_MAP_L2_PROMOTION_L2_256B,
        CU_TENSOR_MAP_FLOAT_OOB_FILL_NONE);
}

extern "C" void kernel_launch(void* const* d_in, const int* in_sizes, int n_in, void* d_out, int out_size) {
    const bf16* x = (const bf16*)d_in[0];
    const bf16* wr = (const bf16*)d_in[1];
    const bf16* wi = (const bf16*)d_in[2];
    const bf16* w1 = (const bf16*)d_in[4];
    const bf16* w2 = (const bf16*)d_in[5];
    const bf16* c = (const bf16*)d_in[6];
    const bf16* wmod = (const bf16*)d_in[7];
    bf16* out = (bf16*)d_out;
    static EncodeFn enc = nullptr;
    static CUtensorMap tw1, tw2a, tw2b, tw2c;
    static const void *pw1 = nullptr, *pw2 = nullptr;
    if (!enc) {
        cudaFuncSetAttribute(k1_kernel, cudaFuncAttributeMaxDynamicSharedMemorySize, (int)sizeof(K1Smem));
        cudaFuncSetAttribute(k2_kernel, cudaFuncAttributeMaxDynamicSharedMemorySize, (int)sizeof(K2Smem));
        cudaFuncSetAttribute(k3_kernel, cudaFuncAttributeMaxDynamicSharedMemorySize, K3_SMEM);
        void* fn = nullptr;
        cudaDriverEntryPointQueryResult qr;
        cudaGetDriverEntryPoint("cuTensorMapEncodeTiled", &fn, cudaEnableDefault, &qr);
        enc = (EncodeFn)fn;
    }
    if (pw1 != w1 || pw2 != w2) {
        make_map(enc, &tw1, w1, 640, 1536, 32, 3);
        make_map(enc, &tw2a, w2, 1536, 640, 32, 3);
        make_map(enc, &tw2b, w2, 1536, 640, 48, 2);
        make_map(enc, &tw2c, w2, 1536, 640, 96, 1);
        pw1 = w1;
        pw2 = w2;
    }
    launch_pdl(k1_kernel, dim3(128), dim3(320), sizeof(K1Smem), false, x, c, wmod);
    launch_pdl(k2_kernel, dim3(129), dim3(320), sizeof(K2Smem), true, wr, wi, c, wmod, w1, w2);
    launch_pdl(k3_kernel, dim3(128), dim3(384), K3_SMEM, true, x, out, tw1, tw2a, tw2b, tw2c);
}
```

```cpp
#include <cuda_runtime.h>
#include <cuda_bf16.h>
#include <cuda.h>
#include <stdint.h>

typedef __nv_bfloat16 bf16;

struct __align__(128) Scratch {
    unsigned int epoch[32];
    unsigned int cnt[16 * 32];
    unsigned int cntP[128 * 40];
    uint4 wm[128];
    unsigned long long mod[4 * 1920];
    uint32_t I[129 * 128 * 40];
    uint4 H[128 * 40 * 32];
    uint4 P[128 * 8 * 20 * 32];
};
__device__ Scratch g_s;
#define g_epoch (scr->epoch)
#define g_cnt (scr->cnt)
#define g_cntP (scr->cntP)
#define g_wm (scr->wm)
#define g_mod (scr->mod)
#define g_I (scr->I)
#define g_H (scr->H)
#define g_P (scr->P)

__device__ __align__(128) const uint32_t g_tab[7168] = {
    0x45000,0x140010,0x240020,0x340030,0x440040,0x540050,0x640060,0x740070,0x840080,0x940090,0xa400a0,0xb400b0,
    0xc400c0,0xd400d0,0xe400e0,0xf400f0,0x1040100,0x1140110,0x1240120,0x1340130,0x1440140,0x1540150,0x1640160,0x1740170,
    0x1840180,0x1940190,0x1a401a0,0x1b401b0,0x1c401c0,0x1d401d0,0x1e401e0,0x1f401f0,0x2040200,0x2140210,0x2240220,0x2340230,
    0x2440240,0x2540250,0x2640260,0x2740270,0x2840280,0x2940290,0x2a402a0,0x2b402b0,0x2c402c0,0x2d402d0,0x2e402e0,0x2f402f0,
    0x3040300,0x3140310,0x3240320,0x3340330,0x3440340,0x3540350,0x3640360,0x3740370,0x3840380,0x3940390,0x3a403a0,0x3b403b0,
    0x3c403c0,0x3d403d0,0x3e403e0,0x3f403f0,0x4040400,0x4140410,0x4240420,0x4340430,0x4440440,0x4540450,0x4640460,0x4740470,
    0x4840480,0x4940490,0x4a404a0,0x4b404b0,0x4c404c0,0x4d404d0,0x4e404e0,0x4f404f0,0x5040500,0x5140510,0x5240520,0x5340530,
    0x5440540,0x5540550,0x5640560,0x5740570,0x5840580,0x5940590,0x5a405a0,0x5b405b0,0x5c405c0,0x5d405d0,0x5e405e0,0x5f405f0,
    0x6040600,0x6140610,0x6240620,0x6340630,0x6440640,0x6540650,0x6640660,0x6740670,0x6840680,0x6940690,0x6a406a0,0x6b406b0,
    0x6c406c0,0x6d406d0,0x6e406e0,0x6f406f0,0x7040700,0x7140710,0x7240720,0x7340730,0x7440740,0x7540750,0x7640760,0x7740770,
    0x7840780,0x7940790,0x7a407a0,0x7b407b0,0x7c407c0,0x7d407d0,0x7e407e0,0x7f407f0,0x8040800,0x8140810,0x8240820,0x8340830,
    0x8440840,0x8540850,0x8640860,0x8740870,0x8840880,0x8940890,0x8a408a0,0x8b408b0,0x8c408c0,0x8d408d0,0x8e408e0,0x8f408f0,
    0x9040900,0x9140910,0x9240920,0x9340930,0x9440940,0x9540950,0x9640960,0x9740970,0x9840980,0x9940990,0x9a409a0,0x9b409b0,
    0x9c409c0,0x9d409d0,0x9e409e0,0x9f409f0,0x9fc5004,0x9ec09f8,0x9dc09e8,0x9cc09d8,0x9bc09c8,0x9ac09b8,0x99c09a8,0x98c0998,
    0x97c0988,0x96c0978,0x95c0968,0x94c0958,0x93c0948,0x92c0938,0x91c0928,0x90c0918,0x8fc0908,0x8ec08f8,0x8dc08e8,0x8cc08d8,
    0x8bc08c8,0x8ac08b8,0x89c08a8,0x88c0898,0x87c0888,0x86c0878,0x85c0868,0x84c0858,0x83c0848,0x82c0838,0x81c0828,0x80c0818,
    0x7fc0808,0x7ec07f8,0x7dc07e8,0x7cc07d8,0x7bc07c8,0x7ac07b8,0x79c07a8,0x78c0798,0x77c0788,0x76c0778,0x75c0768,0x74c0758,
    0x73c0748,0x72c0738,0x71c0728,0x70c0718,0x6fc0708,0x6ec06f8,0x6dc06e8,0x6cc06d8,0x6bc06c8,0x6ac06b8,0x69c06a8,0x68c0698,
    0x67c0688,0x66c0678,0x65c0668,0x64c0658,0x63c0648,0x62c0638,0x61c0628,0x60c0618,0x5fc0608,0x5ec05f8,0x5dc05e8,0x5cc05d8,
    0x5bc05c8,0x5ac05b8,0x59c05a8,0x58c0598,0x57c0588,0x56c0578,0x55c0568,0x54c0558,0x53c0548,0x52c0538,0x51c0528,0x50c0518,
    0x4fc0508,0x4ec04f8,0x4dc04e8,0x4cc04d8,0x4bc04c8,0x4ac04b8,0x49c04a8,0x48c0498,0x47c0488,0x46c0478,0x45c0468,0x44c0458,
    0x43c0448,0x42c0438,0x41c0428,0x40c0418,0x3fc0408,0x3ec03f8,0x3dc03e8,0x3cc03d8,0x3bc03c8,0x3ac03b8,0x39c03a8,0x38c0398,
    0x37c0388,0x36c0378,0x35c0368,0x34c0358,0x33c0348,0x32c0338,0x31c0328,0x30c0318,0x2fc0308,0x2ec02f8,0x2dc02e8,0x2cc02d8,
    0x2bc02c8,0x2ac02b8,0x29c02a8,0x28c0298,0x27c0288,0x26c0278,0x25c0268,0x24c0258,0x23c0248,0x22c0238,0x21c0228,0x20c0218,
    0x1fc0208,0x1ec01f8,0x1dc01e8,0x1cc01d8,0x1bc01c8,0x1ac01b8,0x19c01a8,0x18c0198,0x17c0188,0x16c0178,0x15c0168,0x14c0158,
    0x13c0148,0x12c0138,0x11c0128,0x10c0118,0xfc0108,0xec00f8,0xdc00e8,0xcc00d8,0xbc00c8,0xac00b8,0x9c00a8,0x8c0098,
    0x7c0088,0x6c0078,0x5c0068,0x4c0058,0x3c0048,0x2c0038,0x1c0028,0xc0018,0x200000,0x600040,0x40080,0x440024,
    0x840064,0x280008,0x680048,0xc0088,0x4c002c,0x8c006c,0x300010,0x700050,0x140090,0x540034,0x940074,0x380018,
    0x780058,0x1c0098,0x5c003c,0x9c007c,0xc000a0,0x10000e0,0xa40120,0xe400c4,0x1240104,0xc800a8,0x10800e8,0xac0128,
    0xec00cc,0x12c010c,0xd000b0,0x11000f0,0xb40130,0xf400d4,0x1340114,0xd800b8,0x11800f8,0xbc0138,0xfc00dc,0x13c011c,
    0x1600140,0x1a00180,0x14401c0,0x1840164,0x1c401a4,0x1680148,0x1a80188,0x14c01c8,0x18c016c,0x1cc01ac,0x1700150,0x1b00190,
    0x15401d0,0x1940174,0x1d401b4,0x1780158,0x1b80198,0x15c01d8,0x19c017c,0x1dc01bc,0x20001e0,0x2400220,0x1e40260,0x2240204,
    0x2640244,0x20801e8,0x2480228,0x1ec0268,0x22c020c,0x26c024c,0x21001f0,0x2500230,0x1f40270,0x2340214,0x2740254,0x21801f8,
    0x2580238,0x1fc0278,0x23c021c,0x27c025c,0x2a00280,0x2e002c0,0x2840300,0x2c402a4,0x30402e4,0x2a80288,0x2e802c8,0x28c0308,
    0x2cc02ac,0x30c02ec,0x2b00290,0x2f002d0,0x2940310,0x2d402b4,0x31402f4,0x2b80298,0x2f802d8,0x29c0318,0x2dc02bc,0x31c02fc,
    0x3400320,0x3800360,0x32403a0,0x3640344,0x3a40384,0x3480328,0x3880368,0x32c03a8,0x36c034c,0x3ac038c,0x3500330,0x3900370,
    0x33403b0,0x3740354,0x3b40394,0x3580338,0x3980378,0x33c03b8,0x37c035c,0x3bc039c,0x3e003c0,0x4200400,0x3c40440,0x40403e4,
    0x4440424,0x3e803c8,0x4280408,0x3cc0448,0x40c03ec,0x44c042c,0x3f003d0,0x4300410,0x3d40450,0x41403f4,0x4540434,0x3f803d8,
    0x4380418,0x3dc0458,0x41c03fc,0x45c043c,0x4800460,0x4c004a0,0x46404e0,0x4a40484,0x4e404c4,0x4880468,0x4c804a8,0x46c04e8,
    0x4ac048c,0x4ec04cc,0x4900470,0x4d004b0,0x47404f0,0x4b40494,0x4f404d4,0x4980478,0x4d804b8,0x47c04f8,0x4bc049c,0x4fc04dc,
    0x5200500,0x5600540,0x5040580,0x5440524,0x5840564,0x5280508,0x5680548,0x50c0588,0x54c052c,0x58c056c,0x5300510,0x5700550,
    0x5140590,0x5540534,0x5940574,0x5380518,0x5780558,0x51c0598,0x55c053c,0x59c057c,0x5c005a0,0x60005e0,0x5a40620,0x5e405c4,
    0x6240604,0x5c805a8,0x60805e8,0x5ac0628,0x5ec05cc,0x62c060c,0x5d005b0,0x61005f0,0x5b40630,0x5f405d4,0x6340614,0x5d805b8,
    0x61805f8,0x5bc0638,0x5fc05dc,0x63c061c,0x6600640,0x6a00680,0x64406c0,0x6840664,0x6c406a4,0x6680648,0x6a80688,0x64c06c8,
    0x68c066c,0x6cc06ac,0x6700650,0x6b00690,0x65406d0,0x6940674,0x6d406b4,0x6780658,0x6b80698,0x65c06d8,0x69c067c,0x6dc06bc,
    0x70006e0,0x7400720,0x6e40760,0x7240704,0x7640744,0x70806e8,0x7480728,0x6ec0768,0x72c070c,0x76c074c,0x71006f0,0x7500730,
    0x6f40770,0x7340714,0x7740754,0x71806f8,0x7580738,0x6fc0778,0x73c071c,0x77c075c,0x7a00780,0x7e007c0,0x7840800,0x7c407a4,
    0x80407e4,0x7a80788,0x7e807c8,0x78c0808,0x7cc07ac,0x80c07ec,0x7b00790,0x7f007d0,0x7940810,0x7d407b4,0x81407f4,0x7b80798,
    0x7f807d8,0x79c0818,0x7dc07bc,0x81c07fc,0x8400820,0x8800860,0x82408a0,0x8640844,0x8a40884,0x8480828,0x8880868,0x82c08a8,
    0x86c084c,0x8ac088c,0x8500830,0x8900870,0x83408b0,0x8740854,0x8b40894,0x8580838,0x8980878,0x83c08b8,0x87c085c,0x8bc089c,
    0x8e008c0,0x9200900,0x8c40940,0x90408e4,0x9440924,0x8e808c8,0x9280908,0x8cc0948,0x90c08ec,0x94c092c,0x8f008d0,0x9300910,
    0x8d40950,0x91408f4,0x9540934,0x8f808d8,0x9380918,0x8dc0958,0x91c08fc,0x95c093c,0x9800960,0x9c009a0,0x96409e0,0x9a40984,
    0x9e409c4,0x9880968,0x9c809a8,0x96c09e8,0x9ac098c,0x9ec09cc,0x9900970,0x9d009b0,0x97409f0,0x9b40994,0x9f409d4,0x9980978,
    0x9d809b8,0x97c09f8,0x9bc099c,0x9fc09dc,0x145000,0x40000,0x340030,0x240020,0x540050,0x440040,0x740070,0x640060,
    0x940090,0x840080,0xb400b0,0xa400a0,0xd400d0,0xc400c0,0xf400f0,0xe400e0,0x1140110,0x1040100,0x1340130,0x1240120,
    0x1540150,0x1440140,0x1740170,0x1640160,0x1940190,0x1840180,0x1b401b0,0x1a401a0,0x1d401d0,0x1c401c0,0x1f401f0,0x1e401e0,
    0x2140210,0x2040200,0x2340230,0x2240220,0x2540250,0x2440240,0x2740270,0x2640260,0x2940290,0x2840280,0x2b402b0,0x2a402a0,
    0x2d402d0,0x2c402c0,0x2f402f0,0x2e402e0,0x3140310,0x3040300,0x3340330,0x3240320,0x3540350,0x3440340,0x3740370,0x3640360,
    0x3940390,0x3840380,0x3b403b0,0x3a403a0,0x3d403d0,0x3c403c0,0x3f403f0,0x3e403e0,0x4140410,0x4040400,0x4340430,0x4240420,
    0x4540450,0x4440440,0x4740470,0x4640460,0x4940490,0x4840480,0x4b404b0,0x4a404a0,0x4d404d0,0x4c404c0,0x4f404f0,0x4e404e0,
    0x5140510,0x5040500,0x5340530,0x5240520,0x5540550,0x5440540,0x5740570,0x5640560,0x5940590,0x5840580,0x5b405b0,0x5a405a0,
    0x5d405d0,0x5c405c0,0x5f405f0,0x5e405e0,0x6140610,0x6040600,0x6340630,0x6240620,0x6540650,0x6440640,0x6740670,0x6640660,
    0x6940690,0x6840680,0x6b406b0,0x6a406a0,0x6d406d0,0x6c406c0,0x6f406f0,0x6e406e0,0x7140710,0x7040700,0x7340730,0x7240720,
    0x7540750,0x7440740,0x7740770,0x7640760,0x7940790,0x7840780,0x7b407b0,0x7a407a0,0x7d407d0,0x7c407c0,0x7f407f0,0x7e407e0,
    0x8140810,0x8040800,0x8340830,0x8240820,0x8540850,0x8440840,0x8740870,0x8640860,0x8940890,0x8840880,0x8b408b0,0x8a408a0,
    0x8d408d0,0x8c408c0,0x8f408f0,0x8e408e0,0x9140910,0x9040900,0x9340930,0x9240920,0x9540950,0x9440940,0x9740970,0x9640960,
    0x9940990,0x9840980,0x9b409b0,0x9a409a0,0x9d409d0,0x9c409c0,0x9f409f0,0x9e409e0,0x9ec5004,0x9fc09e8,0x9cc09f8,0x9dc09c8,
    0x9ac09d8,0x9bc09a8,0x98c09b8,0x99c0988,0x96c0998,0x97c0968,0x94c0978,0x95c0948,0x92c0958,0x93c0928,0x90c0938,0x91c0908,
    0x8ec0918,0x8fc08e8,0x8cc08f8,0x8dc08c8,0x8ac08d8,0x8bc08a8,0x88c08b8,0x89c0888,0x86c0898,0x87c0868,0x84c0878,0x85c0848,
    0x82c0858,0x83c0828,0x80c0838,0x81c0808,0x7ec0818,0x7fc07e8,0x7cc07f8,0x7dc07c8,0x7ac07d8,0x7bc07a8,0x78c07b8,0x79c0788,
    0x76c0798,0x77c0768,0x74c0778,0x75c0748,0x72c0758,0x73c0728,0x70c0738,0x71c0708,0x6ec0718,0x6fc06e8,0x6cc06f8,0x6dc06c8,
    0x6ac06d8,0x6bc06a8,0x68c06b8,0x69c0688,0x66c0698,0x67c0668,0x64c0678,0x65c0648,0x62c0658,0x63c0628,0x60c0638,0x61c0608,
    0x5ec0618,0x5fc05e8,0x5cc05f8,0x5dc05c8,0x5ac05d8,0x5bc05a8,0x58c05b8,0x59c0588,0x56c0598,0x57c0568,0x54c0578,0x55c0548,
    0x52c0558,0x53c0528,0x50c0538,0x51c0508,0x4ec0518,0x4fc04e8,0x4cc04f8,0x4dc04c8,0x4ac04d8,0x4bc04a8,0x48c04b8,0x49c0488,
    0x46c0498,0x47c0468,0x44c0478,0x45c0448,0x42c0458,0x43c0428,0x40c0438,0x41c0408,0x3ec0418,0x3fc03e8,0x3cc03f8,0x3dc03c8,
    0x3ac03d8,0x3bc03a8,0x38c03b8,0x39c0388,0x36c0398,0x37c0368,0x34c0378,0x35c0348,0x32c0358,0x33c0328,0x30c0338,0x31c0308,
    0x2ec0318,0x2fc02e8,0x2cc02f8,0x2dc02c8,0x2ac02d8,0x2bc02a8,0x28c02b8,0x29c0288,0x26c0298,0x27c0268,0x24c0278,0x25c0248,
    0x22c0258,0x23c0228,0x20c0238,0x21c0208,0x1ec0218,0x1fc01e8,0x1cc01f8,0x1dc01c8,0x1ac01d8,0x1bc01a8,0x18c01b8,0x19c0188,
    0x16c0198,0x17c0168,0x14c0178,0x15c0148,0x12c0158,0x13c0128,0x10c0138,0x11c0108,0xec0118,0xfc00e8,0xcc00f8,0xdc00c8,
    0xac00d8,0xbc00a8,0x8c00b8,0x9c0088,0x6c0098,0x7c0068,0x4c0078,0x5c0048,0x2c0058,0x3c0028,0xc0038,0x1c0008,
    0x300010,0x700050,0x140090,0x540034,0x940074,0x380018,0x780058,0x1c0098,0x5c003c,0x9c007c,0x200000,0x600040,
    0x40080,0x440024,0x840064,0x280008,0x680048,0xc0088,0x4c002c,0x8c006c,0xd000b0,0x11000f0,0xb40130,0xf400d4,
    0x1340114,0xd800b8,0x11800f8,0xbc0138,0xfc00dc,0x13c011c,0xc000a0,0x10000e0,0xa40120,0xe400c4,0x1240104,0xc800a8,
    0x10800e8,0xac0128,0xec00cc,0x12c010c,0x1700150,0x1b00190,0x15401d0,0x1940174,0x1d401b4,0x1780158,0x1b80198,0x15c01d8,
    0x19c017c,0x1dc01bc,0x1600140,0x1a00180,0x14401c0,0x1840164,0x1c401a4,0x1680148,0x1a80188,0x14c01c8,0x18c016c,0x1cc01ac,
    0x21001f0,0x2500230,0x1f40270,0x2340214,0x2740254,0x21801f8,0x2580238,0x1fc0278,0x23c021c,0x27c025c,0x20001e0,0x2400220,
    0x1e40260,0x2240204,0x2640244,0x20801e8,0x2480228,0x1ec0268,0x22c020c,0x26c024c,0x2b00290,0x2f002d0,0x2940310,0x2d402b4,
    0x31402f4,0x2b80298,0x2f802d8,0x29c0318,0x2dc02bc,0x31c02fc,0x2a00280,0x2e002c0,0x2840300,0x2c402a4,0x30402e4,0x2a80288,
    0x2e802c8,0x28c0308,0x2cc02ac,0x30c02ec,0x3500330,0x3900370,0x33403b0,0x3740354,0x3b40394,0x3580338,0x3980378,0x33c03b8,
    0x37c035c,0x3bc039c,0x3400320,0x3800360,0x32403a0,0x3640344,0x3a40384,0x3480328,0x3880368,0x32c03a8,0x36c034c,0x3ac038c,
    0x3f003d0,0x4300410,0x3d40450,0x41403f4,0x4540434,0x3f803d8,0x4380418,0x3dc0458,0x41c03fc,0x45c043c,0x3e003c0,0x4200400,
    0x3c40440,0x40403e4,0x4440424,0x3e803c8,0x4280408,0x3cc0448,0x40c03ec,0x44c042c,0x4900470,0x4d004b0,0x47404f0,0x4b40494,
    0x4f404d4,0x4980478,0x4d804b8,0x47c04f8,0x4bc049c,0x4fc04dc,0x4800460,0x4c004a0,0x46404e0,0x4a40484,0x4e404c4,0x4880468,
    0x4c804a8,0x46c04e8,0x4ac048c,0x4ec04cc,0x5300510,0x5700550,0x5140590,0x5540534,0x5940574,0x5380518,0x5780558,0x51c0598,
    0x55c053c,0x59c057c,0x5200500,0x5600540,0x5040580,0x5440524,0x5840564,0x5280508,0x5680548,0x50c0588,0x54c052c,0x58c056c,
    0x5d005b0,0x61005f0,0x5b40630,0x5f405d4,0x6340614,0x5d805b8,0x61805f8,0x5bc0638,0x5fc05dc,0x63c061c,0x5c005a0,0x60005e0,
    0x5a40620,0x5e405c4,0x6240604,0x5c805a8,0x60805e8,0x5ac0628,0x5ec05cc,0x62c060c,0x6700650,0x6b00690,0x65406d0,0x6940674,
    0x6d406b4,0x6780658,0x6b80698,0x65c06d8,0x69c067c,0x6dc06bc,0x6600640,0x6a00680,0x64406c0,0x6840664,0x6c406a4,0x6680648,
    0x6a80688,0x64c06c8,0x68c066c,0x6cc06ac,0x71006f0,0x7500730,0x6f40770,0x7340714,0x7740754,0x71806f8,0x7580738,0x6fc0778,
    0x73c071c,0x77c075c,0x70006e0,0x7400720,0x6e40760,0x7240704,0x7640744,0x70806e8,0x7480728,0x6ec0768,0x72c070c,0x76c074c,
    0x7b00790,0x7f007d0,0x7940810,0x7d407b4,0x81407f4,0x7b80798,0x7f807d8,0x79c0818,0x7dc07bc,0x81c07fc,0x7a00780,0x7e007c0,
    0x7840800,0x7c407a4,0x80407e4,0x7a80788,0x7e807c8,0x78c0808,0x7cc07ac,0x80c07ec,0x8500830,0x8900870,0x83408b0,0x8740854,
    0x8b40894,0x8580838,0x8980878,0x83c08b8,0x87c085c,0x8bc089c,0x8400820,0x8800860,0x82408a0,0x8640844,0x8a40884,0x8480828,
    0x8880868,0x82c08a8,0x86c084c,0x8ac088c,0x8f008d0,0x9300910,0x8d40950,0x91408f4,0x9540934,0x8f808d8,0x9380918,0x8dc0958,
    0x91c08fc,0x95c093c,0x8e008c0,0x9200900,0x8c40940,0x90408e4,0x9440924,0x8e808c8,0x9280908,0x8cc0948,0x90c08ec,0x94c092c,
    0x9900970,0x9d009b0,0x97409f0,0x9b40994,0x9f409d4,0x9980978,0x9d809b8,0x97c09f8,0x9bc099c,0x9fc09dc,0x9800960,0x9c009a0,
    0x96409e0,0x9a40984,0x9e409c4,0x9880968,0x9c809a8,0x96c09e8,0x9ac098c,0x9ec09cc,0x3c003c00,0x0,0x0,0x3c003c00,
    0x3c003c00,0x0,0x0,0x3c003c00,0x3c003c00,0x0,0x0,0x3c003c00,0x3c003c00,0x0,0x0,0x3c003c00,
    0x39a83c00,0xb9a80000,0x39a80000,0x39a83c00,0xb9a80000,0xb9a8bc00,0x39a83c00,0xb9a80000,0xb9a8bc00,0x39a80000,0xb9a80000,0xb9a8bc00,
    0x39a80000,0x39a83c00,0xb9a8bc00,0x39a80000,0x3c00,0xbc000000,0x3c000000,0x3c00,0xbc00,0x3c000000,0xbc000000,0xbc00,
    0x3c00,0xbc000000,0x3c000000,0x3c00,0xbc00,0x3c000000,0xbc000000,0xbc00,0xb9a83c00,0xb9a80000,0x39a80000,0xb9a83c00,
    0x39a80000,0xb9a83c00,0x39a8bc00,0x39a80000,0x39a8bc00,0x39a80000,0xb9a80000,0x39a8bc00,0xb9a80000,0x39a8bc00,0xb9a83c00,0xb9a80000,
    0xbc003c00,0x0,0x0,0xbc003c00,0xbc003c00,0x0,0x0,0xbc003c00,0xbc003c00,0x0,0x0,0xbc003c00,
    0xbc003c00,0x0,0x0,0xbc003c00,0xb9a83c00,0x39a80000,0xb9a80000,0xb9a83c00,0x39a80000,0x39a8bc00,0xb9a83c00,0x39a80000,
    0x39a8bc00,0xb9a80000,0x39a80000,0x39a8bc00,0xb9a80000,0xb9a83c00,0x39a8bc00,0xb9a80000,0x3c00,0x3c000000,0xbc000000,0x3c00,
    0xbc00,0xbc000000,0x3c000000,0xbc00,0x3c00,0x3c000000,0xbc000000,0x3c00,0xbc00,0xbc000000,0x3c000000,0xbc00,
    0x39a83c00,0x39a80000,0xb9a80000,0x39a83c00,0xb9a80000,0x39a83c00,0xb9a8bc00,0xb9a80000,0xb9a8bc00,0xb9a80000,0x39a80000,0xb9a8bc00,
    0x39a80000,0xb9a8bc00,0x39a83c00,0x39a80000,0x3c00,0x3c00,0x3c00,0x3c00,0x3c00,0x3c00,0xbc00,0xbc00,
    0x3c00,0x3c00,0x3c00,0x3c00,0x3c00,0x3c00,0xbc00,0xbc00,0x3c000000,0x3c000000,0x3c000000,0x3c000000,
    0x3c000000,0x3c000000,0xbc000000,0xbc000000,0x3c000000,0x3c000000,0x3c000000,0x3c000000,0x3c000000,0x3c000000,0xbc000000,0xbc000000,
    0x3c00,0xbc00,0x3c00,0xbc00,0x39a839a8,0xb9a8b9a8,0xb9a8b9a8,0x39a839a8,0x3c000000,0xbc000000,0x3c000000,0xbc000000,
    0x39a8b9a8,0xb9a839a8,0xb9a839a8,0x39a8b9a8,0x3c000000,0xbc000000,0x3c000000,0xbc000000,0x39a8b9a8,0xb9a839a8,0xb9a839a8,0x39a8b9a8,
    0xbc00,0x3c00,0xbc00,0x3c00,0xb9a8b9a8,0x39a839a8,0x39a839a8,0xb9a8b9a8,0x3c00,0x3c00,0x3c00,0x3c00,
    0x3c000000,0x3c000000,0xbc000000,0xbc000000,0xbc00,0xbc00,0xbc00,0xbc00,0xbc000000,0xbc000000,0x3c000000,0x3c000000,
    0x3c000000,0x3c000000,0x3c000000,0x3c000000,0xbc00,0xbc00,0x3c00,0x3c00,0xbc000000,0xbc000000,0xbc000000,0xbc000000,
    0x3c00,0x3c00,0xbc00,0xbc00,0x3c00,0xbc00,0x3c00,0xbc00,0x39a8b9a8,0xb9a839a8,0xb9a839a8,0x39a8b9a8,
    0xbc000000,0x3c000000,0xbc000000,0x3c000000,0x39a839a8,0xb9a8b9a8,0xb9a8b9a8,0x39a839a8,0x3c000000,0xbc000000,0x3c000000,0xbc000000,
    0xb9a8b9a8,0x39a839a8,0x39a839a8,0xb9a8b9a8,0x3c00,0xbc00,0x3c00,0xbc00,0x39a8b9a8,0xb9a839a8,0xb9a839a8,0x39a8b9a8,
    0x3c00,0x3c00,0x38b43a79,0x38b43a79,0x3c00,0x3c00,0xb8b4ba79,0xb8b4ba79,0x3c00,0x3c00,0x38b43a79,0x38b43a79,
    0x3c00,0x3c00,0xb8b4ba79,0xb8b4ba79,0x3c000000,0x3c000000,0x3a79b8b4,0x3a79b8b4,0x3c000000,0x3c000000,0xba7938b4,0xba7938b4,
    0x3c000000,0x3c000000,0x3a79b8b4,0x3a79b8b4,0x3c000000,0x3c000000,0xba7938b4,0xba7938b4,0x31023be7,0xb102bbe7,0x39a839a8,0xb9a8b9a8,
    0x3a7938b4,0xba79b8b4,0xbc000000,0x3c000000,0x3be7b102,0xbbe73102,0x39a8b9a8,0xb9a839a8,0x38b4ba79,0xb8b43a79,0x3c00,0xbc00,
    0x3be7b102,0xbbe73102,0x39a8b9a8,0xb9a839a8,0x38b4ba79,0xb8b43a79,0x3c00,0xbc00,0xb102bbe7,0x31023be7,0xb9a8b9a8,0x39a839a8,
    0xba79b8b4,0x3a7938b4,0x3c000000,0xbc000000,0x34f23b9c,0x34f23b9c,0x3a7938b4,0x3a7938b4,0x3b9cb4f2,0x3b9cb4f2,0xb8b43a79,0xb8b43a79,
    0xb4f2bb9c,0xb4f2bb9c,0xba79b8b4,0xba79b8b4,0xbb9c34f2,0xbb9c34f2,0x38b4ba79,0x38b4ba79,0x3b9cb4f2,0x3b9cb4f2,0x38b4ba79,0x38b4ba79,
    0xb4f2bb9c,0xb4f2bb9c,0x3a7938b4,0x3a7938b4,0xbb9c34f2,0xbb9c34f2,0xb8b43a79,0xb8b43a79,0x34f23b9c,0x34f23b9c,0xba79b8b4,0xba79b8b4,
    0x37443b21,0xb744bb21,0x3b213744,0xbb21b744,0x34f2bb9c,0xb4f23b9c,0x34f23b9c,0xb4f2bb9c,0xbb213744,0x3b21b744,0xb7443b21,0x3744bb21,
    0x3b9c34f2,0xbb9cb4f2,0xbb9c34f2,0x3b9cb4f2,0x3b21b744,0xbb213744,0x3744bb21,0xb7443b21,0xbb9cb4f2,0x3b9c34f2,0x3b9cb4f2,0xbb9c34f2,
    0x37443b21,0xb744bb21,0x3b213744,0xbb21b744,0x34f2bb9c,0xb4f23b9c,0x34f23b9c,0xb4f2bb9c,0x3c00,0x3c00,0x3b9c34f2,0x3b9c34f2,
    0x3c00,0x3c00,0xbb9cb4f2,0xbb9cb4f2,0x3c00,0x3c00,0x3b9c34f2,0x3b9c34f2,0x3c00,0x3c00,0xbb9cb4f2,0xbb9cb4f2,
    0x3c000000,0x3c000000,0x34f2bb9c,0x34f2bb9c,0x3c000000,0x3c000000,0xb4f23b9c,0xb4f23b9c,0x3c000000,0x3c000000,0x34f2bb9c,0x34f2bb9c,
    0x3c000000,0x3c000000,0xb4f23b9c,0xb4f23b9c,0x34f23b9c,0xb4f2bb9c,0x3c000000,0xbc000000,0x3b213744,0xbb21b744,0xb9a839a8,0x39a8b9a8,
    0x3b9cb4f2,0xbb9c34f2,0xbc00,0x3c00,0x3744bb21,0xb7443b21,0x39a839a8,0xb9a8b9a8,0x3b9cb4f2,0xbb9c34f2,0xbc00,0x3c00,
    0x3744bb21,0xb7443b21,0x39a839a8,0xb9a8b9a8,0xb4f2bb9c,0x34f23b9c,0xbc000000,0x3c000000,0xbb21b744,0x3b213744,0x39a8b9a8,0xb9a839a8,
    0x38b43a79,0x38b43a79,0x3b9cb4f2,0x3b9cb4f2,0x3a79b8b4,0x3a79b8b4,0x34f23b9c,0x34f23b9c,0xb8b4ba79,0xb8b4ba79,0xbb9c34f2,0xbb9c34f2,
    0xba7938b4,0xba7938b4,0xb4f2bb9c,0xb4f2bb9c,0x3a79b8b4,0x3a79b8b4,0xb4f2bb9c,0xb4f2bb9c,0xb8b4ba79,0xb8b4ba79,0x3b9cb4f2,0x3b9cb4f2,
    0xba7938b4,0xba7938b4,0x34f23b9c,0x34f23b9c,0x38b43a79,0x38b43a79,0xbb9c34f2,0xbb9c34f2,0x3a7938b4,0xba79b8b4,0x3a79b8b4,0xba7938b4,
    0xb102bbe7,0x31023be7,0x3be73102,0xbbe7b102,0xb8b43a79,0x38b4ba79,0x38b43a79,0xb8b4ba79,0x3be7b102,0xbbe73102,0xb1023be7,0x3102bbe7,
    0x38b4ba79,0xb8b43a79,0xb8b4ba79,0x38b43a79,0xbbe73102,0x3be7b102,0x3102bbe7,0xb1023be7,0x3a7938b4,0xba79b8b4,0x3a79b8b4,0xba7938b4,
    0xb102bbe7,0x31023be7,0x3be73102,0xbbe7b102,0x3c00,0x3c00,0x3b9cb4f2,0x3b9cb4f2,0x3c00,0x3c00,0xbb9c34f2,0xbb9c34f2,
    0x3c00,0x3c00,0x3b9cb4f2,0x3b9cb4f2,0x3c00,0x3c00,0xbb9c34f2,0xbb9c34f2,0x3c000000,0x3c000000,0xb4f2bb9c,0xb4f2bb9c,
    0x3c000000,0x3c000000,0x34f23b9c,0x34f23b9c,0x3c000000,0x3c000000,0xb4f2bb9c,0xb4f2bb9c,0x3c000000,0x3c000000,0x34f23b9c,0x34f23b9c,
    0x37443b21,0xb744bb21,0x39a8b9a8,0xb9a839a8,0x3b9c34f2,0xbb9cb4f2,0x3c00,0xbc00,0x3b21b744,0xbb213744,0xb9a8b9a8,0x39a839a8,
    0x34f2bb9c,0xb4f23b9c,0x3c000000,0xbc000000,0x3b21b744,0xbb213744,0xb9a8b9a8,0x39a839a8,0x34f2bb9c,0xb4f23b9c,0x3c000000,0xbc000000,
    0xb744bb21,0x37443b21,0xb9a839a8,0x39a8b9a8,0xbb9cb4f2,0x3b9c34f2,0xbc00,0x3c00,0x3a7938b4,0x3a7938b4,0x34f2bb9c,0x34f2bb9c,
    0x38b4ba79,0x38b4ba79,0x3b9c34f2,0x3b9c34f2,0xba79b8b4,0xba79b8b4,0xb4f23b9c,0xb4f23b9c,0xb8b43a79,0xb8b43a79,0xbb9cb4f2,0xbb9cb4f2,
    0x38b4ba79,0x38b4ba79,0xbb9cb4f2,0xbb9cb4f2,0xba79b8b4,0xba79b8b4,0x34f2bb9c,0x34f2bb9c,0xb8b43a79,0xb8b43a79,0x3b9c34f2,0x3b9c34f2,
    0x3a7938b4,0x3a7938b4,0xb4f23b9c,0xb4f23b9c,0x3be73102,0xbbe7b102,0xb102bbe7,0x31023be7,0xb8b4ba79,0x38b43a79,0x38b4ba79,0xb8b43a79,
    0xb1023be7,0x3102bbe7,0x3be7b102,0xbbe73102,0x3a79b8b4,0xba7938b4,0x3a7938b4,0xba79b8b4,0x3102bbe7,0xb1023be7,0xbbe73102,0x3be7b102,
    0xba7938b4,0x3a79b8b4,0xba79b8b4,0x3a7938b4,0x3be73102,0xbbe7b102,0xb102bbe7,0x31023be7,0xb8b4ba79,0x38b43a79,0x38b4ba79,0xb8b43a79,
    0x3c00,0x3c00,0x38b4ba79,0x38b4ba79,0x3c00,0x3c00,0xb8b43a79,0xb8b43a79,0x3c00,0x3c00,0x38b4ba79,0x38b4ba79,
    0x3c00,0x3c00,0xb8b43a79,0xb8b43a79,0x3c000000,0x3c000000,0xba79b8b4,0xba79b8b4,0x3c000000,0x3c000000,0x3a7938b4,0x3a7938b4,
    0x3c000000,0x3c000000,0xba79b8b4,0xba79b8b4,0x3c000000,0x3c000000,0x3a7938b4,0x3a7938b4,0x38b43a79,0xb8b4ba79,0xbc00,0x3c00,
    0x3be73102,0xbbe7b102,0x39a839a8,0xb9a8b9a8,0x3a79b8b4,0xba7938b4,0xbc000000,0x3c000000,0x3102bbe7,0xb1023be7,0x39a8b9a8,0xb9a839a8,
    0x3a79b8b4,0xba7938b4,0xbc000000,0x3c000000,0x3102bbe7,0xb1023be7,0x39a8b9a8,0xb9a839a8,0xb8b4ba79,0x38b43a79,0x3c00,0xbc00,
    0xbbe7b102,0x3be73102,0xb9a8b9a8,0x39a839a8,0x3b9c34f2,0x3b9c34f2,0xb8b4ba79,0xb8b4ba79,0x34f2bb9c,0x34f2bb9c,0x3a79b8b4,0x3a79b8b4,
    0xbb9cb4f2,0xbb9cb4f2,0x38b43a79,0x38b43a79,0xb4f23b9c,0xb4f23b9c,0xba7938b4,0xba7938b4,0x34f2bb9c,0x34f2bb9c,0xba7938b4,0xba7938b4,
    0xbb9cb4f2,0xbb9cb4f2,0xb8b4ba79,0xb8b4ba79,0xb4f23b9c,0xb4f23b9c,0x3a79b8b4,0x3a79b8b4,0x3b9c34f2,0x3b9c34f2,0x38b43a79,0x38b43a79,
    0x3b9cb4f2,0xbb9c34f2,0xbb9cb4f2,0x3b9c34f2,0xbb21b744,0x3b213744,0xb744bb21,0x37443b21,0x34f23b9c,0xb4f2bb9c,0x34f2bb9c,0xb4f23b9c,
    0x3744bb21,0xb7443b21,0x3b21b744,0xbb213744,0xb4f2bb9c,0x34f23b9c,0xb4f23b9c,0x34f2bb9c,0xb7443b21,0x3744bb21,0xbb213744,0x3b21b744,
    0x3b9cb4f2,0xbb9c34f2,0xbb9cb4f2,0x3b9c34f2,0xbb21b744,0x3b213744,0xb744bb21,0x37443b21,0x2c00,0x2c00,0x2c00,0x2c00,
    0x2c00,0x2c00,0x2c00,0x2c00,0x2c00,0x2c00,0x2c00,0x2c00,0x2c00,0x2c00,0x2c00,0x2c00,
    0x2c00,0x2c000000,0xac00,0xac000000,0x261f2b64,0x2b64a61f,0xa61fab64,0xab64261f,0x29a829a8,0x29a8a9a8,0xa9a8a9a8,0xa9a829a8,
    0x2b64261f,0x261fab64,0xab64a61f,0xa61f2b64,0x2c00,0xac00,0x2c00,0xac00,0x29a829a8,0xa9a8a9a8,0x29a829a8,0xa9a8a9a8,
    0x2c000000,0xac000000,0x2c000000,0xac000000,0x29a8a9a8,0xa9a829a8,0x29a8a9a8,0xa9a829a8,0x2c00,0xac000000,0xac00,0x2c000000,
    0x2b64261f,0xa61f2b64,0xab64a61f,0x261fab64,0x29a8a9a8,0x29a829a8,0xa9a829a8,0xa9a8a9a8,0xa61fab64,0x2b64a61f,0x261f2b64,0xab64261f,
    0x2c00,0x2c00,0x2c00,0x2c00,0x2c000000,0x2c000000,0x2c000000,0x2c000000,0xac00,0xac00,0xac00,0xac00,
    0xac000000,0xac000000,0xac000000,0xac000000,0x2c00,0x2c000000,0xac00,0xac000000,0x2b64a61f,0xa61fab64,0xab64261f,0x261f2b64,
    0xa9a8a9a8,0xa9a829a8,0x29a829a8,0x29a8a9a8,0xa61f2b64,0x2b64261f,0x261fab64,0xab64a61f,0x2c00,0xac00,0x2c00,0xac00,
    0x29a8a9a8,0xa9a829a8,0x29a8a9a8,0xa9a829a8,0xac000000,0x2c000000,0xac000000,0x2c000000,0x29a829a8,0xa9a8a9a8,0x29a829a8,0xa9a8a9a8,
    0x2c00,0xac000000,0xac00,0x2c000000,0x261fab64,0x2b64261f,0xa61f2b64,0xab64a61f,0xa9a829a8,0xa9a8a9a8,0x29a8a9a8,0x29a829a8,
    0x2b64a61f,0x261f2b64,0xab64261f,0xa61fab64,0x2c00,0x2c00,0x2c00,0x2c00,0xac00,0xac00,0xac00,0xac00,
    0x2c00,0x2c00,0x2c00,0x2c00,0xac00,0xac00,0xac00,0xac00,0x2c00,0x2c000000,0xac00,0xac000000,
    0xa61fab64,0xab64261f,0x261f2b64,0x2b64a61f,0x29a829a8,0x29a8a9a8,0xa9a8a9a8,0xa9a829a8,0xab64a61f,0xa61f2b64,0x2b64261f,0x261fab64,
    0x2c00,0xac00,0x2c00,0xac00,0xa9a8a9a8,0x29a829a8,0xa9a8a9a8,0x29a829a8,0x2c000000,0xac000000,0x2c000000,0xac000000,
    0xa9a829a8,0x29a8a9a8,0xa9a829a8,0x29a8a9a8,0x2c00,0xac000000,0xac00,0x2c000000,0xab64a61f,0x261fab64,0x2b64261f,0xa61f2b64,
    0x29a8a9a8,0x29a829a8,0xa9a829a8,0xa9a8a9a8,0x261f2b64,0xab64261f,0xa61fab64,0x2b64a61f,0x2c00,0x2c00,0x2c00,0x2c00,
    0xac000000,0xac000000,0xac000000,0xac000000,0xac00,0xac00,0xac00,0xac00,0x2c000000,0x2c000000,0x2c000000,0x2c000000,
    0x2c00,0x2c000000,0xac00,0xac000000,0xab64261f,0x261f2b64,0x2b64a61f,0xa61fab64,0xa9a8a9a8,0xa9a829a8,0x29a829a8,0x29a8a9a8,
    0x261fab64,0xab64a61f,0xa61f2b64,0x2b64261f,0x2c00,0xac00,0x2c00,0xac00,0xa9a829a8,0x29a8a9a8,0xa9a829a8,0x29a8a9a8,
    0xac000000,0x2c000000,0xac000000,0x2c000000,0xa9a8a9a8,0x29a829a8,0xa9a8a9a8,0x29a829a8,0x2c00,0xac000000,0xac00,0x2c000000,
    0xa61f2b64,0xab64a61f,0x261fab64,0x2b64261f,0xa9a829a8,0xa9a8a9a8,0x29a8a9a8,0x29a829a8,0xab64261f,0xa61fab64,0x2b64a61f,0x261f2b64,
    0x2c000000,0x2c000000,0x2c000000,0x2c000000,0x2c000000,0x2c000000,0x2c000000,0x2c000000,0x2c000000,0x2c000000,0x2c000000,0x2c000000,
    0x2c000000,0x2c000000,0x2c000000,0x2c000000,0x2c000000,0xac00,0xac000000,0x2c00,0x2b64a61f,0xa61fab64,0xab64261f,0x261f2b64,
    0x29a8a9a8,0xa9a8a9a8,0xa9a829a8,0x29a829a8,0x261fab64,0xab64a61f,0xa61f2b64,0x2b64261f,0x2c000000,0xac000000,0x2c000000,0xac000000,
    0x29a8a9a8,0xa9a829a8,0x29a8a9a8,0xa9a829a8,0xac00,0x2c00,0xac00,0x2c00,0xa9a8a9a8,0x29a829a8,0xa9a8a9a8,0x29a829a8,
    0x2c000000,0x2c00,0xac000000,0xac00,0x261fab64,0x2b64261f,0xa61f2b64,0xab64a61f,0xa9a8a9a8,0x29a8a9a8,0x29a829a8,0xa9a829a8,
    0xab64261f,0xa61fab64,0x2b64a61f,0x261f2b64,0x2c000000,0x2c000000,0x2c000000,0x2c000000,0xac00,0xac00,0xac00,0xac00,
    0xac000000,0xac000000,0xac000000,0xac000000,0x2c00,0x2c00,0x2c00,0x2c00,0x2c000000,0xac00,0xac000000,0x2c00,
    0xa61fab64,0xab64261f,0x261f2b64,0x2b64a61f,0xa9a829a8,0x29a829a8,0x29a8a9a8,0xa9a8a9a8,0x2b64261f,0x261fab64,0xab64a61f,0xa61f2b64,
    0x2c000000,0xac000000,0x2c000000,0xac000000,0xa9a8a9a8,0x29a829a8,0xa9a8a9a8,0x29a829a8,0x2c00,0xac00,0x2c00,0xac00,
    0x29a8a9a8,0xa9a829a8,0x29a8a9a8,0xa9a829a8,0x2c000000,0x2c00,0xac000000,0xac00,0xab64a61f,0x261fab64,0x2b64261f,0xa61f2b64,
    0x29a829a8,0xa9a829a8,0xa9a8a9a8,0x29a8a9a8,0xa61fab64,0x2b64a61f,0x261f2b64,0xab64261f,0x2c000000,0x2c000000,0x2c000000,0x2c000000,
    0xac000000,0xac000000,0xac000000,0xac000000,0x2c000000,0x2c000000,0x2c000000,0x2c000000,0xac000000,0xac000000,0xac000000,0xac000000,
    0x2c000000,0xac00,0xac000000,0x2c00,0xab64261f,0x261f2b64,0x2b64a61f,0xa61fab64,0x29a8a9a8,0xa9a8a9a8,0xa9a829a8,0x29a829a8,
    0xa61f2b64,0x2b64261f,0x261fab64,0xab64a61f,0x2c000000,0xac000000,0x2c000000,0xac000000,0xa9a829a8,0x29a8a9a8,0xa9a829a8,0x29a8a9a8,
    0xac00,0x2c00,0xac00,0x2c00,0x29a829a8,0xa9a8a9a8,0x29a829a8,0xa9a8a9a8,0x2c000000,0x2c00,0xac000000,0xac00,
    0xa61f2b64,0xab64a61f,0x261fab64,0x2b64261f,0xa9a8a9a8,0x29a8a9a8,0x29a829a8,0xa9a829a8,0x2b64a61f,0x261f2b64,0xab64261f,0xa61fab64,
    0x2c000000,0x2c000000,0x2c000000,0x2c000000,0x2c00,0x2c00,0x2c00,0x2c00,0xac000000,0xac000000,0xac000000,0xac000000,
    0xac00,0xac00,0xac00,0xac00,0x2c000000,0xac00,0xac000000,0x2c00,0x261f2b64,0x2b64a61f,0xa61fab64,0xab64261f,
    0xa9a829a8,0x29a829a8,0x29a8a9a8,0xa9a8a9a8,0xab64a61f,0xa61f2b64,0x2b64261f,0x261fab64,0x2c000000,0xac000000,0x2c000000,0xac000000,
    0x29a829a8,0xa9a8a9a8,0x29a829a8,0xa9a8a9a8,0x2c00,0xac00,0x2c00,0xac00,0xa9a829a8,0x29a8a9a8,0xa9a829a8,0x29a8a9a8,
    0x2c000000,0x2c00,0xac000000,0xac00,0x2b64261f,0xa61f2b64,0xab64a61f,0x261fab64,0x29a829a8,0xa9a829a8,0xa9a8a9a8,0x29a8a9a8,
    0x261f2b64,0xab64261f,0xa61fab64,0x2b64a61f,0x2c000000,0x29a8a9a8,0xac00,0xa9a8a9a8,0x2bd9a23e,0x2872aaa7,0xa23eabd9,0xaaa7a872,
    0x2b64a61f,0x261fab64,0xa61fab64,0xab64a61f,0x2aa7a872,0x223eabd9,0xa872aaa7,0xabd9a23e,0x2c000000,0xa9a8a9a8,0x2c00,0x29a8a9a8,
    0x2aa7a872,0xabd9a23e,0x28722aa7,0x223eabd9,0x261fab64,0xab64261f,0x2b64261f,0xa61fab64,0xa23eabd9,0xa8722aa7,0x2bd9a23e,0xaaa7a872,
    0x2c000000,0xa9a829a8,0xac00,0x29a829a8,0x2872aaa7,0x223e2bd9,0xaaa7a872,0x2bd9a23e,0xa61fab64,0x2b64261f,0xab64261f,0x261fab64,
    0xabd9a23e,0x2aa7a872,0xa23e2bd9,0xa872aaa7,0x2c000000,0x29a829a8,0x2c00,0xa9a829a8,0x223eabd9,0x2aa7a872,0x2bd9223e,0x28722aa7,
    0xab64a61f,0xa61fab64,0x261fab64,0x2b64a61f,0xa8722aa7,0xabd9223e,0xaaa7a872,0xa23eabd9,0x2c000000,0x29a8a9a8,0xac00,0xa9a8a9a8,
    0xa23eabd9,0xaaa7a872,0xabd9223e,0xa8722aa7,0xab64261f,0xa61f2b64,0x261f2b64,0x2b64261f,0x28722aa7,0x2bd9223e,0x2aa7a872,0x223eabd9,
    0x2c000000,0xa9a8a9a8,0x2c00,0x29a8a9a8,0xa872aaa7,0xa23e2bd9,0x2aa7a872,0xabd9a23e,0xa61f2b64,0x2b64a61f,0xab64a61f,0x261f2b64,
    0x2bd9a23e,0xaaa7a872,0x223e2bd9,0x2872aaa7,0x2c000000,0xa9a829a8,0xac00,0x29a829a8,0xaaa7a872,0x2bd9a23e,0xa8722aa7,0xa23eabd9,
    0x261f2b64,0xab64a61f,0x2b64a61f,0xa61f2b64,0x223eabd9,0x28722aa7,0xabd9a23e,0x2aa7a872,0x2c000000,0x29a829a8,0x2c00,0xa9a829a8,
    0xabd9a23e,0xa872aaa7,0x223eabd9,0x2aa7a872,0x2b64261f,0x261f2b64,0xa61f2b64,0xab64261f,0xaaa7a872,0xa23eabd9,0x2872aaa7,0x2bd9a23e,
    0x2c000000,0x29a8a9a8,0xac00,0xa9a8a9a8,0xabd9223e,0xa8722aa7,0x223e2bd9,0x2aa72872,0x2b64a61f,0x261fab64,0xa61fab64,0xab64a61f,
    0xaaa72872,0xa23e2bd9,0x28722aa7,0x2bd9223e,0x2c000000,0xa9a8a9a8,0x2c00,0x29a8a9a8,0xaaa72872,0x2bd9223e,0xa872aaa7,0xa23e2bd9,
    0x261fab64,0xab64261f,0x2b64261f,0xa61fab64,0x223e2bd9,0x2872aaa7,0xabd9223e,0x2aa72872,0x2c000000,0xa9a829a8,0xac00,0x29a829a8,
    0xa8722aa7,0xa23eabd9,0x2aa72872,0xabd9223e,0xa61fab64,0x2b64261f,0xab64261f,0x261fab64,0x2bd9223e,0xaaa72872,0x223eabd9,0x28722aa7,
    0x2c000000,0x29a829a8,0x2c00,0xa9a829a8,0xa23e2bd9,0xaaa72872,0xabd9a23e,0xa872aaa7,0xab64a61f,0xa61fab64,0x261fab64,0x2b64a61f,
    0x2872aaa7,0x2bd9a23e,0x2aa72872,0x223e2bd9,0x2c000000,0x29a8a9a8,0xac00,0xa9a8a9a8,0x223e2bd9,0x2aa72872,0x2bd9a23e,0x2872aaa7,
    0xab64261f,0xa61f2b64,0x261f2b64,0x2b64261f,0xa872aaa7,0xabd9a23e,0xaaa72872,0xa23e2bd9,0x2c000000,0xa9a8a9a8,0x2c00,0x29a8a9a8,
    0x28722aa7,0x223eabd9,0xaaa72872,0x2bd9223e,0xa61f2b64,0x2b64a61f,0xab64a61f,0x261f2b64,0xabd9223e,0x2aa72872,0xa23eabd9,0xa8722aa7,
    0x2c000000,0xa9a829a8,0xac00,0x29a829a8,0x2aa72872,0xabd9223e,0x2872aaa7,0x223e2bd9,0x261f2b64,0xab64a61f,0x2b64a61f,0xa61f2b64,
    0xa23e2bd9,0xa872aaa7,0x2bd9223e,0xaaa72872,0x2c000000,0x29a829a8,0x2c00,0xa9a829a8,0x2bd9223e,0x28722aa7,0xa23e2bd9,0xaaa72872,
    0x2b64261f,0x261f2b64,0xa61f2b64,0xab64261f,0x2aa72872,0x223e2bd9,0xa8722aa7,0xabd9223e,0xac00,0xa9a8a9a8,0xac000000,0xa9a829a8,
    0xa23eabd9,0xaaa7a872,0xabd9223e,0xa8722aa7,0xa61fab64,0xab64a61f,0xab64261f,0xa61f2b64,0xa872aaa7,0xabd9a23e,0xaaa72872,0xa23e2bd9,
    0xac00,0xa9a829a8,0x2c000000,0xa9a8a9a8,0xa872aaa7,0xa23e2bd9,0x2aa7a872,0xabd9a23e,0xab64a61f,0x261f2b64,0x261fab64,0xab64261f,
    0xabd9223e,0x2aa72872,0xa23eabd9,0xa8722aa7,0xac00,0x29a829a8,0xac000000,0x29a8a9a8,0xaaa7a872,0x2bd9a23e,0xa8722aa7,0xa23eabd9,
    0xab64261f,0x261fab64,0x261f2b64,0xab64a61f,0xa23e2bd9,0xa872aaa7,0x2bd9223e,0xaaa72872,0xac00,0x29a8a9a8,0x2c000000,0x29a829a8,
    0xabd9a23e,0xa872aaa7,0x223eabd9,0x2aa7a872,0xa61f2b64,0xab64261f,0xab64a61f,0xa61fab64,0x2aa72872,0x223e2bd9,0xa8722aa7,0xabd9223e,
    0xac00,0xa9a8a9a8,0xac000000,0xa9a829a8,0xabd9223e,0xa8722aa7,0x223e2bd9,0x2aa72872,0x261f2b64,0x2b64261f,0x2b64a61f,0x261fab64,
    0x2aa7a872,0x223eabd9,0xa872aaa7,0xabd9a23e,0xac00,0xa9a829a8,0x2c000000,0xa9a8a9a8,0xaaa72872,0x2bd9223e,0xa872aaa7,0xa23e2bd9,
    0x2b64261f,0xa61fab64,0xa61f2b64,0x2b64a61f,0xa23eabd9,0xa8722aa7,0x2bd9a23e,0xaaa7a872,0xac00,0x29a829a8,0xac000000,0x29a8a9a8,
    0xa8722aa7,0xa23eabd9,0x2aa72872,0xabd9223e,0x2b64a61f,0xa61f2b64,0xa61fab64,0x2b64261f,0xabd9a23e,0x2aa7a872,0xa23e2bd9,0xa872aaa7,
    0xac00,0x29a8a9a8,0x2c000000,0x29a829a8,0xa23e2bd9,0xaaa72872,0xabd9a23e,0xa872aaa7,0x261fab64,0x2b64a61f,0x2b64261f,0x261f2b64,
    0xa8722aa7,0xabd9223e,0xaaa7a872,0xa23eabd9,0xac00,0xa9a8a9a8,0xac000000,0xa9a829a8,0x223e2bd9,0x2aa72872,0x2bd9a23e,0x2872aaa7,
    0xa61fab64,0xab64a61f,0xab64261f,0xa61f2b64,0x28722aa7,0x2bd9223e,0x2aa7a872,0x223eabd9,0xac00,0xa9a829a8,0x2c000000,0xa9a8a9a8,
    0x28722aa7,0x223eabd9,0xaaa72872,0x2bd9223e,0xab64a61f,0x261f2b64,0x261fab64,0xab64261f,0x2bd9a23e,0xaaa7a872,0x223e2bd9,0x2872aaa7,
    0xac00,0x29a829a8,0xac000000,0x29a8a9a8,0x2aa72872,0xabd9223e,0x2872aaa7,0x223e2bd9,0xab64261f,0x261fab64,0x261f2b64,0xab64a61f,
    0x223eabd9,0x28722aa7,0xabd9a23e,0x2aa7a872,0xac00,0x29a8a9a8,0x2c000000,0x29a829a8,0x2bd9223e,0x28722aa7,0xa23e2bd9,0xaaa72872,
    0xa61f2b64,0xab64261f,0xab64a61f,0xa61fab64,0xaaa7a872,0xa23eabd9,0x2872aaa7,0x2bd9a23e,0xac00,0xa9a8a9a8,0xac000000,0xa9a829a8,
    0x2bd9a23e,0x2872aaa7,0xa23eabd9,0xaaa7a872,0x261f2b64,0x2b64261f,0x2b64a61f,0x261fab64,0xaaa72872,0xa23e2bd9,0x28722aa7,0x2bd9223e,
    0xac00,0xa9a829a8,0x2c000000,0xa9a8a9a8,0x2aa7a872,0xabd9a23e,0x28722aa7,0x223eabd9,0x2b64261f,0xa61fab64,0xa61f2b64,0x2b64a61f,
    0x223e2bd9,0x2872aaa7,0xabd9223e,0x2aa72872,0xac00,0x29a829a8,0xac000000,0x29a8a9a8,0x2872aaa7,0x223e2bd9,0xaaa7a872,0x2bd9a23e,
    0x2b64a61f,0xa61f2b64,0xa61fab64,0x2b64261f,0x2bd9223e,0xaaa72872,0x223eabd9,0x28722aa7,0xac00,0x29a8a9a8,0x2c000000,0x29a829a8,
    0x223eabd9,0x2aa7a872,0x2bd9223e,0x28722aa7,0x261fab64,0x2b64a61f,0x2b64261f,0x261f2b64,0x2872aaa7,0x2bd9a23e,0x2aa72872,0x223e2bd9,
    0x28002800,0x28002800,0x0,0x0,0x28002800,0x28002800,0x0,0x0,0x28002800,0x28002800,0x0,0x0,
    0x28002800,0x28002800,0x0,0x0,0x0,0x0,0x28002800,0x28002800,0x0,0x0,0x28002800,0x28002800,
    0x0,0x0,0x28002800,0x28002800,0x0,0x0,0x28002800,0x28002800,0x27642800,0xa764a800,0xa21f0000,0x221f0000,
    0x221f25a8,0xa21fa5a8,0xa764a5a8,0x276425a8,0xa21f0000,0x221f0000,0xa764a800,0x27642800,0xa764a5a8,0x276425a8,0xa21fa5a8,0x221f25a8,
    0x221f0000,0xa21f0000,0x27642800,0xa764a800,0x276425a8,0xa764a5a8,0x221f25a8,0xa21fa5a8,0x27642800,0xa764a800,0xa21f0000,0x221f0000,
    0x221f25a8,0xa21fa5a8,0xa764a5a8,0x276425a8,0x25a82800,0x25a82800,0xa5a80000,0xa5a80000,0xa5a80000,0xa5a80000,0xa5a8a800,0xa5a8a800,
    0xa5a8a800,0xa5a8a800,0x25a80000,0x25a80000,0x25a80000,0x25a80000,0x25a82800,0x25a82800,0x25a80000,0x25a80000,0x25a82800,0x25a82800,
    0x25a82800,0x25a82800,0xa5a80000,0xa5a80000,0xa5a80000,0xa5a80000,0xa5a8a800,0xa5a8a800,0xa5a8a800,0xa5a8a800,0x25a80000,0x25a80000,
    0x221f2800,0xa21fa800,0xa7640000,0x27640000,0xa764a5a8,0x276425a8,0x221fa5a8,0xa21f25a8,0x27640000,0xa7640000,0x221f2800,0xa21fa800,
    0xa21f25a8,0x221fa5a8,0xa764a5a8,0x276425a8,0x27640000,0xa7640000,0x221f2800,0xa21fa800,0xa21f25a8,0x221fa5a8,0xa764a5a8,0x276425a8,
    0xa21fa800,0x221f2800,0x27640000,0xa7640000,0x276425a8,0xa764a5a8,0xa21f25a8,0x221fa5a8,0x2800,0x2800,0xa8000000,0xa8000000,
    0xa800,0xa800,0x28000000,0x28000000,0x2800,0x2800,0xa8000000,0xa8000000,0xa800,0xa800,0x28000000,0x28000000,
    0x28000000,0x28000000,0x2800,0x2800,0xa8000000,0xa8000000,0xa800,0xa800,0x28000000,0x28000000,0x2800,0x2800,
    0xa8000000,0xa8000000,0xa800,0xa800,0xa21f2800,0x221fa800,0xa7640000,0x27640000,0x2764a5a8,0xa76425a8,0x221f25a8,0xa21fa5a8,
    0xa7640000,0x27640000,0x221fa800,0xa21f2800,0x221f25a8,0xa21fa5a8,0xa76425a8,0x2764a5a8,0x27640000,0xa7640000,0xa21f2800,0x221fa800,
    0xa21fa5a8,0x221f25a8,0x2764a5a8,0xa76425a8,0xa21f2800,0x221fa800,0xa7640000,0x27640000,0x2764a5a8,0xa76425a8,0x221f25a8,0xa21fa5a8,
    0xa5a82800,0xa5a82800,0xa5a80000,0xa5a80000,0x25a80000,0x25a80000,0xa5a82800,0xa5a82800,0x25a8a800,0x25a8a800,0x25a80000,0x25a80000,
    0xa5a80000,0xa5a80000,0x25a8a800,0x25a8a800,0x25a80000,0x25a80000,0xa5a82800,0xa5a82800,0x25a8a800,0x25a8a800,0x25a80000,0x25a80000,
    0xa5a80000,0xa5a80000,0x25a8a800,0x25a8a800,0xa5a82800,0xa5a82800,0xa5a80000,0xa5a80000,0xa7642800,0x2764a800,0xa21f0000,0x221f0000,
    0xa21f25a8,0x221fa5a8,0xa76425a8,0x2764a5a8,0x221f0000,0xa21f0000,0xa7642800,0x2764a800,0x2764a5a8,0xa76425a8,0xa21f25a8,0x221fa5a8,
    0x221f0000,0xa21f0000,0xa7642800,0x2764a800,0x2764a5a8,0xa76425a8,0xa21f25a8,0x221fa5a8,0x2764a800,0xa7642800,0x221f0000,0xa21f0000,
    0x221fa5a8,0xa21f25a8,0x2764a5a8,0xa76425a8,0xa8002800,0xa8002800,0x0,0x0,0xa8002800,0xa8002800,0x0,0x0,
    0xa8002800,0xa8002800,0x0,0x0,0xa8002800,0xa8002800,0x0,0x0,0x0,0x0,0xa8002800,0xa8002800,
    0x0,0x0,0xa8002800,0xa8002800,0x0,0x0,0xa8002800,0xa8002800,0x0,0x0,0xa8002800,0xa8002800,
    0xa7642800,0x2764a800,0x221f0000,0xa21f0000,0xa21f25a8,0x221fa5a8,0x2764a5a8,0xa76425a8,0x221f0000,0xa21f0000,0x2764a800,0xa7642800,
    0x2764a5a8,0xa76425a8,0x221fa5a8,0xa21f25a8,0xa21f0000,0x221f0000,0xa7642800,0x2764a800,0xa76425a8,0x2764a5a8,0xa21f25a8,0x221fa5a8,
    0xa7642800,0x2764a800,0x221f0000,0xa21f0000,0xa21f25a8,0x221fa5a8,0x2764a5a8,0xa76425a8,0xa5a82800,0xa5a82800,0x25a80000,0x25a80000,
    0x25a80000,0x25a80000,0x25a8a800,0x25a8a800,0x25a8a800,0x25a8a800,0xa5a80000,0xa5a80000,0xa5a80000,0xa5a80000,0xa5a82800,0xa5a82800,
    0xa5a80000,0xa5a80000,0xa5a82800,0xa5a82800,0xa5a82800,0xa5a82800,0x25a80000,0x25a80000,0x25a80000,0x25a80000,0x25a8a800,0x25a8a800,
    0x25a8a800,0x25a8a800,0xa5a80000,0xa5a80000,0xa21f2800,0x221fa800,0x27640000,0xa7640000,0x2764a5a8,0xa76425a8,0xa21fa5a8,0x221f25a8,
    0xa7640000,0x27640000,0xa21f2800,0x221fa800,0x221f25a8,0xa21fa5a8,0x2764a5a8,0xa76425a8,0xa7640000,0x27640000,0xa21f2800,0x221fa800,
    0x221f25a8,0xa21fa5a8,0x2764a5a8,0xa76425a8,0x221fa800,0xa21f2800,0xa7640000,0x27640000,0xa76425a8,0x2764a5a8,0x221f25a8,0xa21fa5a8,
    0x2800,0x2800,0x28000000,0x28000000,0xa800,0xa800,0xa8000000,0xa8000000,0x2800,0x2800,0x28000000,0x28000000,
    0xa800,0xa800,0xa8000000,0xa8000000,0xa8000000,0xa8000000,0x2800,0x2800,0x28000000,0x28000000,0xa800,0xa800,
    0xa8000000,0xa8000000,0x2800,0x2800,0x28000000,0x28000000,0xa800,0xa800,0x221f2800,0xa21fa800,0x27640000,0xa7640000,
    0xa764a5a8,0x276425a8,0xa21f25a8,0x221fa5a8,0x27640000,0xa7640000,0xa21fa800,0x221f2800,0xa21f25a8,0x221fa5a8,0x276425a8,0xa764a5a8,
    0xa7640000,0x27640000,0x221f2800,0xa21fa800,0x221fa5a8,0xa21f25a8,0xa764a5a8,0x276425a8,0x221f2800,0xa21fa800,0x27640000,0xa7640000,
    0xa764a5a8,0x276425a8,0xa21f25a8,0x221fa5a8,0x25a82800,0x25a82800,0x25a80000,0x25a80000,0xa5a80000,0xa5a80000,0x25a82800,0x25a82800,
    0xa5a8a800,0xa5a8a800,0xa5a80000,0xa5a80000,0x25a80000,0x25a80000,0xa5a8a800,0xa5a8a800,0xa5a80000,0xa5a80000,0x25a82800,0x25a82800,
    0xa5a8a800,0xa5a8a800,0xa5a80000,0xa5a80000,0x25a80000,0x25a80000,0xa5a8a800,0xa5a8a800,0x25a82800,0x25a82800,0x25a80000,0x25a80000,
    0x27642800,0xa764a800,0x221f0000,0xa21f0000,0x221f25a8,0xa21fa5a8,0x276425a8,0xa764a5a8,0xa21f0000,0x221f0000,0x27642800,0xa764a800,
    0xa764a5a8,0x276425a8,0x221f25a8,0xa21fa5a8,0xa21f0000,0x221f0000,0x27642800,0xa764a800,0xa764a5a8,0x276425a8,0x221f25a8,0xa21fa5a8,
    0xa764a800,0x27642800,0xa21f0000,0x221f0000,0xa21fa5a8,0x221f25a8,0xa764a5a8,0x276425a8,0x0,0x0,0xa800a800,0xa800a800,
    0x0,0x0,0xa800a800,0xa800a800,0x0,0x0,0xa800a800,0xa800a800,0x0,0x0,0xa800a800,0xa800a800,
    0x28002800,0x28002800,0x0,0x0,0x28002800,0x28002800,0x0,0x0,0x28002800,0x28002800,0x0,0x0,
    0x28002800,0x28002800,0x0,0x0,0xa4729e3e,0x24721e3e,0xa6a7a7d9,0x26a727d9,0xa7d9a6a7,0x27d926a7,0x9e3ea472,0x1e3e2472,
    0xa6a7a7d9,0x26a727d9,0x24721e3e,0xa4729e3e,0x9e3ea472,0x1e3e2472,0x27d926a7,0xa7d9a6a7,0x26a727d9,0xa6a7a7d9,0xa4729e3e,0x24721e3e,
    0x1e3e2472,0x9e3ea472,0xa7d9a6a7,0x27d926a7,0xa4729e3e,0x24721e3e,0xa6a7a7d9,0x26a727d9,0xa7d9a6a7,0x27d926a7,0x9e3ea472,0x1e3e2472,
    0xa764a21f,0xa764a21f,0xa21fa764,0xa21fa764,0xa21fa764,0xa21fa764,0x2764221f,0x2764221f,0x2764221f,0x2764221f,0x221f2764,0x221f2764,
    0x221f2764,0x221f2764,0xa764a21f,0xa764a21f,0x221f2764,0x221f2764,0xa764a21f,0xa764a21f,0xa764a21f,0xa764a21f,0xa21fa764,0xa21fa764,
    0xa21fa764,0xa21fa764,0x2764221f,0x2764221f,0x2764221f,0x2764221f,0x221f2764,0x221f2764,0xa7d9a472,0x27d92472,0x1e3ea6a7,0x9e3e26a7,
    0x26a79e3e,0xa6a71e3e,0x247227d9,0xa472a7d9,0x9e3e26a7,0x1e3ea6a7,0xa7d9a472,0x27d92472,0xa472a7d9,0x247227d9,0x26a79e3e,0xa6a71e3e,
    0x9e3e26a7,0x1e3ea6a7,0xa7d9a472,0x27d92472,0xa472a7d9,0x247227d9,0x26a79e3e,0xa6a71e3e,0x27d92472,0xa7d9a472,0x9e3e26a7,0x1e3ea6a7,
    0xa6a71e3e,0x26a79e3e,0xa472a7d9,0x247227d9,0xa5a8a5a8,0xa5a8a5a8,0x25a8a5a8,0x25a8a5a8,0x25a825a8,0x25a825a8,0xa5a825a8,0xa5a825a8,
    0xa5a8a5a8,0xa5a8a5a8,0x25a8a5a8,0x25a8a5a8,0x25a825a8,0x25a825a8,0xa5a825a8,0xa5a825a8,0xa5a825a8,0xa5a825a8,0xa5a8a5a8,0xa5a8a5a8,
    0x25a8a5a8,0x25a8a5a8,0x25a825a8,0x25a825a8,0xa5a825a8,0xa5a825a8,0xa5a8a5a8,0xa5a8a5a8,0x25a8a5a8,0x25a8a5a8,0x25a825a8,0x25a825a8,
    0x9e3ea6a7,0x1e3e26a7,0x27d9a472,0xa7d92472,0xa47227d9,0x2472a7d9,0xa6a79e3e,0x26a71e3e,0x27d9a472,0xa7d92472,0x1e3e26a7,0x9e3ea6a7,
    0xa6a79e3e,0x26a71e3e,0x2472a7d9,0xa47227d9,0xa7d92472,0x27d9a472,0x9e3ea6a7,0x1e3e26a7,0x26a71e3e,0xa6a79e3e,0xa47227d9,0x2472a7d9,
    0x9e3ea6a7,0x1e3e26a7,0x27d9a472,0xa7d92472,0xa47227d9,0x2472a7d9,0xa6a79e3e,0x26a71e3e,0x221fa764,0x221fa764,0x2764a21f,0x2764a21f,
    0xa764221f,0xa764221f,0x221fa764,0x221fa764,0xa21f2764,0xa21f2764,0xa764221f,0xa764221f,0x2764a21f,0x2764a21f,0xa21f2764,0xa21f2764,
    0xa764221f,0xa764221f,0x221fa764,0x221fa764,0xa21f2764,0xa21f2764,0xa764221f,0xa764221f,0x2764a21f,0x2764a21f,0xa21f2764,0xa21f2764,
    0x221fa764,0x221fa764,0x2764a21f,0x2764a21f,0x26a7a7d9,0xa6a727d9,0x24729e3e,0xa4721e3e,0x1e3ea472,0x9e3e2472,0x27d9a6a7,0xa7d926a7,
    0xa4721e3e,0x24729e3e,0x26a7a7d9,0xa6a727d9,0xa7d926a7,0x27d9a6a7,0x1e3ea472,0x9e3e2472,0xa4721e3e,0x24729e3e,0x26a7a7d9,0xa6a727d9,
    0xa7d926a7,0x27d9a6a7,0x1e3ea472,0x9e3e2472,0xa6a727d9,0x26a7a7d9,0xa4721e3e,0x24729e3e,0x9e3e2472,0x1e3ea472,0xa7d926a7,0x27d9a6a7,
    0x2800a800,0x2800a800,0x0,0x0,0x2800a800,0x2800a800,0x0,0x0,0x2800a800,0x2800a800,0x0,0x0,
    0x2800a800,0x2800a800,0x0,0x0,0x0,0x0,0x2800a800,0x2800a800,0x0,0x0,0x2800a800,0x2800a800,
    0x0,0x0,0x2800a800,0x2800a800,0x0,0x0,0x2800a800,0x2800a800,0x26a7a7d9,0xa6a727d9,0xa4721e3e,0x24729e3e,
    0x1e3ea472,0x9e3e2472,0xa7d926a7,0x27d9a6a7,0xa4721e3e,0x24729e3e,0xa6a727d9,0x26a7a7d9,0xa7d926a7,0x27d9a6a7,0x9e3e2472,0x1e3ea472,
    0x24729e3e,0xa4721e3e,0x26a7a7d9,0xa6a727d9,0x27d9a6a7,0xa7d926a7,0x1e3ea472,0x9e3e2472,0x26a7a7d9,0xa6a727d9,0xa4721e3e,0x24729e3e,
    0x1e3ea472,0x9e3e2472,0xa7d926a7,0x27d9a6a7,0x221fa764,0x221fa764,0xa764221f,0xa764221f,0xa764221f,0xa764221f,0xa21f2764,0xa21f2764,
    0xa21f2764,0xa21f2764,0x2764a21f,0x2764a21f,0x2764a21f,0x2764a21f,0x221fa764,0x221fa764,0x2764a21f,0x2764a21f,0x221fa764,0x221fa764,
    0x221fa764,0x221fa764,0xa764221f,0xa764221f,0xa764221f,0xa764221f,0xa21f2764,0xa21f2764,0xa21f2764,0xa21f2764,0x2764a21f,0x2764a21f,
    0x9e3ea6a7,0x1e3e26a7,0xa7d92472,0x27d9a472,0xa47227d9,0x2472a7d9,0x26a71e3e,0xa6a79e3e,0x27d9a472,0xa7d92472,0x9e3ea6a7,0x1e3e26a7,
    0xa6a79e3e,0x26a71e3e,0xa47227d9,0x2472a7d9,0x27d9a472,0xa7d92472,0x9e3ea6a7,0x1e3e26a7,0xa6a79e3e,0x26a71e3e,0xa47227d9,0x2472a7d9,
    0x1e3e26a7,0x9e3ea6a7,0x27d9a472,0xa7d92472,0x2472a7d9,0xa47227d9,0xa6a79e3e,0x26a71e3e,0xa5a8a5a8,0xa5a8a5a8,0xa5a825a8,0xa5a825a8,
    0x25a825a8,0x25a825a8,0x25a8a5a8,0x25a8a5a8,0xa5a8a5a8,0xa5a8a5a8,0xa5a825a8,0xa5a825a8,0x25a825a8,0x25a825a8,0x25a8a5a8,0x25a8a5a8,
    0x25a8a5a8,0x25a8a5a8,0xa5a8a5a8,0xa5a8a5a8,0xa5a825a8,0xa5a825a8,0x25a825a8,0x25a825a8,0x25a8a5a8,0x25a8a5a8,0xa5a8a5a8,0xa5a8a5a8,
    0xa5a825a8,0xa5a825a8,0x25a825a8,0x25a825a8,0xa7d9a472,0x27d92472,0x9e3e26a7,0x1e3ea6a7,0x26a79e3e,0xa6a71e3e,0xa472a7d9,0x247227d9,
    0x9e3e26a7,0x1e3ea6a7,0x27d92472,0xa7d9a472,0xa472a7d9,0x247227d9,0xa6a71e3e,0x26a79e3e,0x1e3ea6a7,0x9e3e26a7,0xa7d9a472,0x27d92472,
    0x247227d9,0xa472a7d9,0x26a79e3e,0xa6a71e3e,0xa7d9a472,0x27d92472,0x9e3e26a7,0x1e3ea6a7,0x26a79e3e,0xa6a71e3e,0xa472a7d9,0x247227d9,
    0xa764a21f,0xa764a21f,0x221f2764,0x221f2764,0xa21fa764,0xa21fa764,0xa764a21f,0xa764a21f,0x2764221f,0x2764221f,0xa21fa764,0xa21fa764,
    0x221f2764,0x221f2764,0x2764221f,0x2764221f,0xa21fa764,0xa21fa764,0xa764a21f,0xa764a21f,0x2764221f,0x2764221f,0xa21fa764,0xa21fa764,
    0x221f2764,0x221f2764,0x2764221f,0x2764221f,0xa764a21f,0xa764a21f,0x221f2764,0x221f2764,0xa4729e3e,0x24721e3e,0x26a727d9,0xa6a7a7d9,
    0xa7d9a6a7,0x27d926a7,0x1e3e2472,0x9e3ea472,0xa6a7a7d9,0x26a727d9,0xa4729e3e,0x24721e3e,0x9e3ea472,0x1e3e2472,0xa7d9a6a7,0x27d926a7,
    0xa6a7a7d9,0x26a727d9,0xa4729e3e,0x24721e3e,0x9e3ea472,0x1e3e2472,0xa7d9a6a7,0x27d926a7,0x24721e3e,0xa4729e3e,0xa6a7a7d9,0x26a727d9,
    0x27d926a7,0xa7d9a6a7,0x9e3ea472,0x1e3e2472,0x30003000,0x80008000,0x30003000,0x80008000,0x30003000,0x80008000,0x30003000,0x80008000,
    0x30003000,0x80008000,0x30003000,0x80008000,0x30003000,0x80008000,0x30003000,0x80008000,0x2ffe3000,0x9e488000,0x2f3b2f64,0xaad7aa1f,
    0x2fea2ff6,0xa4b2a246,0x2edd2f0e,0xac1dab8b,0x2fc32fd9,0xa7c6a63e,0x2e6d2ea7,0xacc4ac72,0x2f882fa8,0xa964a8a5,0x2ded2e2f,0xad5fad13,
    0x2ff63000,0xa2468000,0x2d132da8,0xae2fada8,0x2fa82fd9,0xa8a5a63e,0x2b8b2c72,0xaf0eaea7,0x2f0e2f64,0xab8baa1f,0x28a52a1f,0xafa8af64,
    0x2e2f2ea7,0xad13ac72,0x2246263e,0xaff6afd9,0x2fea3000,0xa4b28000,0x27c62a1f,0xafc3af64,0x2f3b2fa8,0xaad7a8a5,0x9e482246,0xaffeaff6,
    0x2ded2ea7,0xad5fac72,0xa964a63e,0xaf88afd9,0x2c1d2d13,0xaeddae2f,0xacc4ab8b,0xae6daf0e,0x2fd93000,0xa63e8000,0xa63e0000,0xafd9b000,
    0x2ea72f64,0xac72aa1f,0xac72aa1f,0xaea7af64,0x2c722da8,0xaea7ada8,0xaea7ada8,0xac72ada8,0x263e2a1f,0xafd9af64,0xafd9af64,0xa63eaa1f,
    0x2fc33000,0xa7c68000,0xacc4aa1f,0xae6daf64,0x2ded2f0e,0xad5fab8b,0xaf3bae2f,0xaad7ad13,0x29642c72,0xaf88aea7,0xaffeafd9,0x1e48a63e,
    0xa4b22246,0xafeaaff6,0xaeddafa8,0x2c1d28a5,0x2fa83000,0xa8a58000,0xaf0eada8,0xab8bada8,0x2d132ea7,0xae2fac72,0xaff6afd9,0x2246a63e,
    0x22462a1f,0xaff6af64,0xae2faf64,0x2d132a1f,0xab8ba63e,0xaf0eafd9,0xa8a5ac72,0x2fa82ea7,0x2f883000,0xa9648000,0xaffeaf64,0x9e48aa1f,
    0x2c1d2e2f,0xaeddad13,0xae6dafa8,0x2cc428a5,0xa4b2263e,0xafeaafd9,0xa7c6ac72,0x2fc32ea7,0xadedab8b,0xad5faf0e,0x2ad72246,0x2f3b2ff6,
    0x30003000,0x80008000,0x30003000,0x80008000,0x30003000,0x80008000,0x30003000,0x80008000,0x30003000,0x80008000,0x30003000,0x80008000,
    0x30003000,0x80008000,0x30003000,0x80008000,0x2ffa2fff,0xa0b59a48,0x2f252f50,0xab32aa7c,0x2fe22ff1,0xa579a3d6,0x2ec22ef6,0xac48abe3,
    0x2fb62fce,0xa844a703,0x2e4f2e8a,0xacecac9b,0x2f772f99,0xa9c2a905,0x2dcb2e0f,0xad84ad3a,0x2fea2ffe,0xa4b29e48,0x2cc42d5f,0xae6daded,
    0x2f882fc3,0xa964a7c6,0x2ad72c1d,0xaf3baedd,0x2edd2f3b,0xac1daad7,0x27c62964,0xafc3af88,0x2ded2e6d,0xad5facc4,0x1e4824b2,0xaffeafea,
    0x2fce2ffa,0xa703a0b5,0x25792905,0xafe2af99,0x2ef62f77,0xabe3a9c2,0xa3d61a48,0xaff1afff,0x2d842e4f,0xadcbacec,0xaa7ca844,0xaf50afb6,
    0x2b322c9b,0xaf25ae8a,0xad3aac48,0xae0faec2,0x2fa82ff6,0xa8a5a246,0xa8a5a246,0xafa8aff6,0x2e2f2f0e,0xad13ab8b,0xad13ab8b,0xae2faf0e,
    0x2b8b2d13,0xaf0eae2f,0xaf0eae2f,0xab8bad13,0x224628a5,0xaff6afa8,0xaff6afa8,0xa246a8a5,0x2f772ff1,0xa9c2a3d6,0xad84abe3,0xadcbaef6,
    0x2d3a2e8a,0xae0fac9b,0xaf99aec2,0xa905ac48,0x27032b32,0xafceaf25,0xafe2affa,0x2579a0b5,0xa8449a48,0xafb6afff,0xae4faf50,0x2cec2a7c,
    0x2f3b2fea,0xaad7a4b2,0xaf88ae6d,0xa964acc4,0x2c1d2ded,0xaeddad5f,0xafc3affe,0x27c69e48,0x9e4827c6,0xaffeafc3,0xad5faedd,0x2ded2c1d,
    0xacc4a964,0xae6daf88,0xa4b2aad7,0x2fea2f3b,0x2ef62fe2,0xabe3a579,0xaff1afce,0x23d6a703,0x29c22d3a,0xaf77ae0f,0xad84af25,0x2dcb2b32,
    0xa9051a48,0xaf99afff,0xa0b5aa7c,0x2ffa2f50,0xaec2acec,0xac48ae4f,0x2c9b2844,0x2e8a2fb6,0x3c003c00,0x0,0x3b643c00,0x361f0000,
    0x3c003c00,0x0,0x361f39a8,0x3b6439a8,0x3c003c00,0x0,0xb61f0000,0x3b643c00,0x3c003c00,0x0,0xbb64b9a8,0x361f39a8,
    0x3bfe3c00,0x2a480000,0x3b3b3c00,0x36d70000,0x3bea3bf6,0x30b22e46,0x33c63913,0x3bc33a2f,0x3bc33bd9,0x33c6323e,0xb8c4b23e,0x3a6d3bd9,
    0x3b883ba8,0x356434a5,0xbbfebb0e,0x2a48378b,0x3bf63c00,0x2e460000,0x3b0e3c00,0x378b0000,0x3ba83bd9,0x34a5323e,0x2e463872,0x3bf63aa7,
    0x3b0e3b64,0x378b361f,0xba2fb61f,0x39133b64,0x3a2f3aa7,0x39133872,0xbba8bbd9,0xb4a5323e,0x3bea3c00,0x30b20000,0x3add3c00,0x381d0000,
    0x3b3b3ba8,0x36d734a5,0xaa48378b,0x3bfe3b0e,0x39ed3aa7,0x395f3872,0xbb3bb872,0x36d73aa7,0x381d3913,0x3add3a2f,0xba6dbbf6,0xb8c4ae46,
    0x3bd93c00,0x323e0000,0x3aa73c00,0x38720000,0x3aa73b64,0x3872361f,0xb23e361f,0x3bd93b64,0x387239a8,0x3aa739a8,0xbbd9b9a8,0x323e39a8,
    0x323e361f,0x3bd93b64,0xb872bb64,0xbaa7b61f,0x3bc33c00,0x33c60000,0x3a6d3c00,0x38c40000,0x39ed3b0e,0x395f378b,0xb56434a5,0x3b883ba8,
    0x35643872,0x3b883aa7,0xbbfebaa7,0xaa483872,0xb0b22e46,0x3bea3bf6,0xb3c6ba2f,0xbbc3b913,0x3ba83c00,0x34a50000,0x3a2f3c00,0x39130000,
    0x39133aa7,0x3a2f3872,0xb78b323e,0x3b0e3bd9,0x2e46361f,0x3bf63b64,0xbba8bb64,0xb4a5361f,0xb78bb23e,0x3b0e3bd9,0x2e46b872,0xbbf6baa7,
    0x3b883c00,0x35640000,0x39ed3c00,0x395f0000,0x381d3a2f,0x3add3913,0xb8c42e46,0x3a6d3bf6,0xb0b2323e,0x3bea3bd9,0xbaddbbd9,0xb81d323e,
    0xb9edb78b,0x395f3b0e,0x36d7b4a5,0xbb3bbba8,0x3bff3c00,0x26480000,0x3b503c00,0x367c0000,0x3bfa3bfe,0x2cb52a48,0x3505395f,0x3b9939ed,
    0x3bf13bf6,0x2fd62e46,0xb7e3ae46,0x3af63bf6,0x3be23bea,0x317930b2,0xbbceba6d,0x330338c4,0x3bfa3c00,0x2cb50000,0x3b253c00,0x37320000,
    0x3bce3bea,0x330330b2,0x317938c4,0x3be23a6d,0x3b773ba8,0x35c234a5,0xb984b4a5,0x39cb3ba8,0x3af63b3b,0x37e336d7,0xbbf1bb88,0xafd63564,
    0x3bf13c00,0x2fd60000,0x3af63c00,0x37e30000,0x3b773bc3,0x35c233c6,0x2648381d,0x3bff3add,0x3a8a3b0e,0x389b378b,0xbac2b78b,0x38483b0e,
    0x393a39ed,0x3a0f395f,0xbb25bbfe,0xb7322a48,0x3be23c00,0x31790000,0x3ac23c00,0x38480000,0x3af63b88,0x37e33564,0xafd636d7,0x3bf13b3b,
    0x393a3a2f,0x3a0f3913,0xbb99b913,0x35053a2f,0x35c2381d,0x3b773add,0xb984bbc3,0xb9cbb3c6,0x3bce3c00,0x33030000,0x3a8a3c00,0x389b0000,
    0x3a4f3b3b,0x38ec36d7,0xb4443564,0x3bb63b88,0x37323913,0x3b253a2f,0xbbfaba2f,0x2cb53913,0x264833c6,0x3bff3bc3,0xb67cbadd,0xbb50b81d,
    0x3bb63c00,0x34440000,0x3a4f3c00,0x38ec0000,0x39843add,0x39cb381d,0xb67c33c6,0x3b503bc3,0x3303378b,0x3bce3b0e,0xbbe2bb0e,0xb179378b,
    0xb505aa48,0x3b993bfe,0xacb5b95f,0xbbfab9ed,0x3b993c00,0x35050000,0x3a0f3c00,0x393a0000,0x389b3a6d,0x3a8a38c4,0xb84830b2,0x3ac23bea,
    0xa64834a5,0x3bff3ba8,0xbb50bba8,0xb67c34a5,0xb8ecb564,0x3a4f3b88,0x3444b6d7,0xbbb6bb3b,0x3b773c00,0x35c20000,0x39cb3c00,0x39840000,
    0x373239ed,0x3b25395f,0xb93a2a48,0x3a0f3bfe,0xb4442e46,0x3bb63bf6,0xba4fbbf6,0xb8ec2e46,0xbac2b8c4,0x38483a6d,0x389bb0b2,0xba8abbea,
    0x3c00,0x3c00,0x3c00,0x2a483bfe,0x3c00,0x361f3b64,0x3c00,0x36d73b3b,0x3c00,0x39a839a8,0x3c00,0x39ed395f,
    0x3c00,0x3b64361f,0x3c00,0x3b883564,0x3c00,0x3c00,0x2e463bf6,0x30b23bea,0x39a839a8,0x3b64361f,0x3a2f3913,0x3bc333c6,
    0x3c000000,0x39a8b9a8,0x3bf6ae46,0x38c4ba6d,0x39a8b9a8,0xb61fbb64,0x3913ba2f,0xb81dbadd,0x3c00,0x3c00,0x323e3bd9,0x33c63bc3,
    0x3c000000,0x3b64b61f,0x3bd9b23e,0x3a6db8c4,0xbc00,0xb9a8b9a8,0xb23ebbd9,0xbaddb81d,0xbc000000,0xb61f3b64,0xbbd9323e,0xb0b23bea,
    0x3c00,0x3c00,0x34a53ba8,0x35643b88,0x39a8b9a8,0x361fbb64,0x378bbb0e,0x2a48bbfe,0xbc000000,0xb9a839a8,0xbba834a5,0xb6d73b3b,
    0x39a839a8,0x3b64b61f,0x3b0e378b,0x39edb95f,0x3c00,0x3c00,0x361f3b64,0x36d73b3b,0xbc00,0xb61fbb64,0xb61fbb64,0xb9edb95f,
    0x3c00,0x39a839a8,0x361f3b64,0x3b883564,0xbc00,0xbb64b61f,0xb61fbb64,0xbbfe2a48,0x3c00,0x3c00,0x378b3b0e,0x381d3add,
    0xb9a8b9a8,0xbb64b61f,0xbba8b4a5,0xbbea30b2,0x3c000000,0x39a8b9a8,0x3b0eb78b,0x33c6bbc3,0xb9a839a8,0x361f3b64,0xb4a53ba8,0x3a6d38c4,
    0x3c00,0x3c00,0x38723aa7,0x38c43a6d,0xbc000000,0xbb64361f,0xbaa73872,0xb81d3add,0xbc00,0xb9a8b9a8,0xb872baa7,0xbbeab0b2,
    0x3c000000,0x361fbb64,0x3aa7b872,0xb3c6bbc3,0x3c00,0x3c00,0x39133a2f,0x395f39ed,0xb9a839a8,0xb61f3b64,0xae463bf6,0x35643b88,
    0xbc000000,0xb9a839a8,0xba2f3913,0xaa483bfe,0xb9a8b9a8,0xbb64361f,0xbbf6ae46,0xb6d73b3b,0x3c00,0x2e463bf6,0x3c00,0x30b23bea,
    0x3c00,0x378b3b0e,0x3c00,0x381d3add,0x3c00,0x3a2f3913,0x3c00,0x3a6d38c4,0x3c00,0x3ba834a5,0x3c00,0x3bc333c6,
    0x323e3bd9,0x34a53ba8,0x34a53ba8,0x36d73b3b,0x3aa73872,0x3bf62e46,0x3b0e378b,0x3bfeaa48,0x3bd9b23e,0x378bbb0e,0x3ba8b4a5,0x3564bb88,
    0x3872baa7,0xb913ba2f,0x378bbb0e,0xb9edb95f,0x361f3b64,0x378b3b0e,0x38723aa7,0x395f39ed,0x3b64b61f,0x3913ba2f,0x3aa7b872,0x36d7bb3b,
    0xb61fbb64,0xbba8b4a5,0xb872baa7,0xbbfeaa48,0xbb64361f,0x2e463bf6,0xbaa73872,0x35643b88,0x38723aa7,0x39133a2f,0x3a2f3913,0x3add381d,
    0x323ebbd9,0xb4a5bba8,0xae46bbf6,0xb8c4ba6d,0xbaa73872,0xae463bf6,0xb9133a2f,0x33c63bc3,0x3bd9323e,0x378bbb0e,0x3bf6ae46,0x30b2bbea,
    0x39a839a8,0x3a2f3913,0x3b64361f,0x3bc333c6,0xb9a8b9a8,0xbba8b4a5,0xbb64b61f,0xbbea30b2,0x39a839a8,0x3bf6ae46,0x3b64361f,0x3addb81d,
    0xb9a8b9a8,0xbb0e378b,0xbb64b61f,0xb8c43a6d,0x3aa73872,0x3b0e378b,0x3bf62e46,0x3bfeaa48,0xbbd9323e,0xba2f3913,0xba2f3913,0xb5643b88,
    0x3872baa7,0xb4a5bba8,0x2e46bbf6,0xb9edb95f,0x323e3bd9,0x3bf62e46,0x39133a2f,0x3b3bb6d7,0x3b64361f,0x3ba834a5,0x3bd9b23e,0x3b88b564,
    0xb61f3b64,0x2e463bf6,0x323e3bd9,0x395f39ed,0xbb64b61f,0xbb0e378b,0xbbd9323e,0xb6d73b3b,0x361fbb64,0xba2fb913,0xb23ebbd9,0xbbfeaa48,
    0x3bd9323e,0x3bf62e46,0x3b0eb78b,0x3a6db8c4,0x38723aa7,0x3b0e378b,0x3ba834a5,0x3bc3b3c6,0xb23e3bd9,0x39133a2f,0x378b3b0e,0x3bea30b2,
    0xbaa73872,0x34a53ba8,0xb4a53ba8,0x3add381d,0x3c00,0x323e3bd9,0x3c00,0x33c63bc3,0x3c00,0x38723aa7,0x3c00,0x38c43a6d,
    0x3c00,0x3aa73872,0x3c00,0x3add381d,0x3c00,0x3bd9323e,0x3c00,0x3bea30b2,0x361f3b64,0x38723aa7,0x378b3b0e,0x395f39ed,
    0x3b64361f,0x3bd9b23e,0x3ba834a5,0x3b88b564,0x3b64b61f,0x323ebbd9,0x3b0eb78b,0x2a48bbfe,0x361fbb64,0xbaa7b872,0x34a5bba8,0xbb3bb6d7,
    0x39a839a8,0x3aa73872,0x3aa73872,0x3b883564,0x39a8b9a8,0x323ebbd9,0x3872baa7,0xaa48bbfe,0xb9a8b9a8,0xbbd9323e,0xbaa7b872,0xbb3b36d7,
    0xb9a839a8,0x38723aa7,0xb8723aa7,0x39ed395f,0x3b64361f,0x3bd9323e,0x3bf62e46,0x3beab0b2,0xb61fbb64,0xbaa7b872,0xb913ba2f,0xbbc3b3c6,
    0xb61f3b64,0x38723aa7,0xae463bf6,0x3a6d38c4,0x3b64b61f,0xb23ebbd9,0x3a2fb913,0xb81dbadd,0x3c000000,0x3bd9b23e,0x3b64b61f,0x3a6db8c4,
    0xbc000000,0xbaa73872,0xbb64361f,0xb81d3add,0x3c000000,0x3872baa7,0x3b64b61f,0x30b2bbea,0xbc000000,0xb23e3bd9,0xbb64361f,0x33c63bc3,
    0x3b64b61f,0x3aa7b872,0x3913ba2f,0x36d7bb3b,0xb61f3b64,0x323e3bd9,0x2e463bf6,0x395f39ed,0xb61fbb64,0xbbd9b23e,0xba2fb913,0xbb883564,
    0x3b64361f,0x3872baa7,0x3bf6ae46,0x2a48bbfe,0x39a8b9a8,0x3872baa7,0x323ebbd9,0xaa48bbfe,0x39a839a8,0x3bd9323e,0x3bd9323e,0x3b3bb6d7,
    0xb9a839a8,0x323e3bd9,0xb23e3bd9,0x39ed395f,0xb9a8b9a8,0xbaa73872,0xbbd9b23e,0xb5643b88,0x361fbb64,0x323ebbd9,0xb4a5bba8,0xb81dbadd,
    0x3b64b61f,0x3872baa7,0x378bbb0e,0xb0b2bbea,0x3b64361f,0x3aa7b872,0x3ba8b4a5,0x33c6bbc3,0x361f3b64,0x3bd9b23e,0x3b0e378b,0x38c4ba6d,
    0x3c00,0x34a53ba8,0x3c00,0x35643b88,0x3c00,0x39133a2f,0x3c00,0x395f39ed,0x3c00,0x3b0e378b,0x3c00,0x3b3b36d7,
    0x3c00,0x3bf62e46,0x3c00,0x3bfe2a48,0x38723aa7,0x3a2f3913,0x39133a2f,0x3add381d,0x3bd9323e,0x3b0eb78b,0x3bf62e46,0x3a6db8c4,
    0x3aa7b872,0xae46bbf6,0x3a2fb913,0xb3c6bbc3,0x323ebbd9,0xbba8b4a5,0x2e46bbf6,0xbbeab0b2,0x3b64361f,0x3bf62e46,0x3bd9323e,0x3beab0b2,
    0x361fbb64,0xb4a5bba8,0x323ebbd9,0xb81dbadd,0xbb64b61f,0xba2f3913,0xbbd9b23e,0xb8c43a6d,0xb61f3b64,0x3b0e378b,0xb23e3bd9,0x3bc333c6,
    0x3bd9b23e,0x3b0eb78b,0x3b0eb78b,0x395fb9ed,0xbaa7b872,0xbbf62e46,0xbba8b4a5,0xbb3b36d7,0x323e3bd9,0x3ba834a5,0x378b3b0e,0x3bfeaa48,
    0x3872baa7,0xba2fb913,0x34a5bba8,0xbb88b564,0x39a8b9a8,0x378bbb0e,0x361fbb64,0x2a48bbfe,0xb9a839a8,0xae463bf6,0xb61f3b64,0x35643b88,
    0x39a8b9a8,0xb4a5bba8,0x361fbb64,0xb95fb9ed,0xb9a839a8,0x39133a2f,0xb61f3b64,0x3b3b36d7,0x323ebbd9,0xae46bbf6,0xb4a5bba8,0xb8c4ba6d,
    0x38723aa7,0x3ba834a5,0x3b0e378b,0x3bc3b3c6,0xbbd9b23e,0xb9133a2f,0xbba834a5,0xb0b23bea,0x3aa7b872,0xb78bbb0e,0x378bbb0e,0xbaddb81d,
    0xb61fbb64,0xb913ba2f,0xbaa7b872,0xbbc3b3c6,0x3b64b61f,0x378bbb0e,0x3872baa7,0xb0b2bbea,0x361f3b64,0x3bf62e46,0x3aa73872,0x3addb81d,
    0xbb64361f,0x34a53ba8,0xb8723aa7,0x3a6d38c4,0xbaa7b872,0xbba8b4a5,0xbbf62e46,0xbb3b36d7,0xb23ebbd9,0xba2fb913,0xba2fb913,0xbbfe2a48,
    0x3872baa7,0xb78bbb0e,0xae46bbf6,0xbb88b564,0x3bd9b23e,0xae46bbf6,0x3913ba2f,0xb9edb95f,0x3c00,0x21073c00,0x3c00,0x2b893bfc,
    0x3c00,0x36453b5c,0x3c00,0x36fc3b33,0x3c00,0x39b6399a,0x3c00,0x39fb3950,0x3c00,0x3b6c35fa,0x3c00,0x3b8f353e,
    0x25073c00,0x278a3bff,0x2f863bf2,0x31a03be0,0x39c4398b,0x3b7a35af,0x3a4838f4,0x3bd032dc,0x3c00a507,0x397db9d2,0x3bf2af86,0x3893ba90,
    0x398bb9c4,0xb68ebb4c,0x38f4ba48,0xb850babd,0x29063bfe,0x2a483bfe,0x33783bc7,0x34a53ba8,0x3bfea906,0x3b3bb6d7,0x3bc7b378,0x3a2fb913,
    0xa906bbfe,0xb9edb95f,0xb378bbc7,0xbb0eb78b,0xbbfe2906,0xb5643b88,0xbbc73378,0xae463bf6,0x2b893bfc,0x2c653bfb,0x358a3b81,0x36693b54,
    0x3950b9fb,0x3518bb95,0x36b3bb44,0xa507bc00,0xbbfc2b89,0xb9413a08,0xbb81358a,0xb5d53b73,0x39fb3950,0x3b2ab720,0x3b4436b3,0x398bb9c4,
    0x2d053bfa,0x2da63bf8,0x37443b21,0x380c3ae7,0xad05bbfa,0xb767bb18,0xb744bb21,0xba61b8d4,0x2d053bfa,0x3a223923,0x37443b21,0x3bbe340a,
    0xad05bbfa,0xbba2b4cb,0xb744bb21,0xbbed3062,0x2e463bf6,0x2ee63bf4,0x38723aa7,0x38d43a61,0xba2fb913,0xbbaeb47e,0xbbd9b23e,0xbbbe340a,
    0x3bf6ae46,0x3904ba3c,0x3aa7b872,0x3062bbed,0xb9133a2f,0x37ae3b05,0xb23e3bd9,0x3ae7380c,0x2f863bf2,0x30133bef,0x39323a15,0x398b39c4,
    0xbbf22f86,0xbaf137f4,0xba153932,0xb6693b54,0xaf86bbf2,0xba55b8e4,0xb932ba15,0xbc00a507,0x3bf2af86,0x3431bbb8,0x3a15b932,0xb5d5bb73,
    0x30623bed,0x30b23bea,0x39e0396e,0x3a2f3913,0xb8d43a61,0xb3c63bc3,0x29063bfe,0x378b3b0e,0xbbed3062,0xb8c43a6d,0xb96e39e0,0x2e463bf6,
    0xba61b8d4,0xbadd381d,0xbbfe2906,0xb4a53ba8,0x3c00,0x2ee63bf4,0x3c00,0x31023be7,0x3c00,0x37ae3b05,0x3c00,0x382e3ad2,
    0x3c00,0x3a3c3904,0x3c00,0x3a7938b4,0x3c00,0x3bae347e,0x3c00,0x3bc73378,0x32dc3bd0,0x35183b95,0x34f23b9c,0x37443b21,
    0x3abd3850,0x3bfb2c65,0x3b213744,0x3bfaad05,0x3bd0b2dc,0x3720bb2a,0x3b9cb4f2,0x34f2bb9c,0x3850babd,0xb941ba08,0x3744bb21,0xba15b932,
    0x36b33b44,0x381d3add,0x38b43a79,0x39a839a8,0x3b44b6b3,0x38c4ba6d,0x3a79b8b4,0x361fbb64,0xb6b3bb44,0xbbc3b3c6,0xb8b4ba79,0xbc000000,
    0xbb4436b3,0x30b23bea,0xba7938b4,0x361f3b64,0x38d43a61,0x397d39d2,0x3a7938b4,0x3b213744,0x3062bbed,0xb5afbb7a,0xb102bbe7,0xb932ba15,
    0xba6138d4,0xa78a3bff,0xb8b43a79,0x34f23b9c,0x3bed3062,0x368ebb4c,0x3be7b102,0x2d05bbfa,0x3a153932,0x3a9c3882,0x3b9c34f2,0x3be73102,
    0xba15b932,0xbbd5b28d,0xbb9cb4f2,0xbbc73378,0x3a153932,0x3bdcb1ef,0x3b9c34f2,0x3a79b8b4,0xba15b932,0xbab23861,0xbb9cb4f2,0xb82e3ad2,
    0x3b0e378b,0x3b6c35fa,0x3c000000,0x3be7b102,0xbba834a5,0xb99a39b6,0xb9a839a8,0xb3783bc7,0x378bbb0e,0xb645bb5c,0xbc00,0xba79b8b4,
    0x34a53ba8,0x3c00a107,0x39a839a8,0x3ad2b82e,0x3bb33458,0x3be43151,0x3b9cb4f2,0x3b21b744,0xb4583bb3,0x332a3bcc,0x34f23b9c,0x3a153932,
    0xbbb3b458,0xba8538a3,0xbb9c34f2,0xb4f23b9c,0x3458bbb3,0xbac8b83f,0xb4f2bb9c,0xbbfa2d05,0x3bfc2b89,0x3bfeaa48,0x3a79b8b4,0x39a8b9a8,
    0x395039fb,0x3b883564,0x3be73102,0x3b64b61f,0xab893bfc,0x39ed395f,0x38b43a79,0x3c000000,0xb9fb3950,0x36d73b3b,0xb1023be7,0x3b64361f,
    0x3c00,0x328d3bd5,0x3c00,0x340a3bbe,0x3c00,0x38823a9c,0x3c00,0x38d43a61,0x3c00,0x3ab23861,0x3c00,0x3ae7380c,
    0x3c00,0x3bdc31ef,0x3c00,0x3bed3062,0x36693b54,0x38a33a85,0x37d13afb,0x398b39c4,0x3b7335d5,0x3bccb32a,0x3bb33458,0x3b73b5d5,
    0x3b54b669,0x3151bbe4,0x3afbb7d1,0x2507bc00,0x35d5bb73,0xbac8b83f,0x3458bbb3,0xbb54b669,0x39e0396e,0x3add381d,0x3ad2382e,0x3ba834a5,
    0x396eb9e0,0x30b2bbea,0x382ebad2,0xae46bbf6,0xb9e0b96e,0xbbc333c6,0xbad2b82e,0xbb0e378b,0xb96e39e0,0x38c43a6d,0xb82e3ad2,0x3a2f3913,
    0x3b8f353e,0x3bef3013,0x3bfe2906,0x3bd0b2dc,0xb6fcbb33,0xbaf1b7f4,0xb96eb9e0,0xbbe0b1a0,0xb53e3b8f,0x38e43a55,0xa9063bfe,0x3abd3850,
    0x3b33b6fc,0xb431bbb8,0x39e0b96e,0xb893ba90,0x3bfaad05,0x3baeb47e,0x3b21b744,0x39fbb950,0xbbfa2d05,0xba3c3904,0xbb213744,0xb6fc3b33,
    0x3bfaad05,0x37aebb05,0x3b21b744,0x2b89bbfc,0xbbfa2d05,0xaee63bf4,0xbb213744,0x353e3b8f,0x3b0eb78b,0x3a22b923,0x3872baa7,0x353ebb8f,
    0xb4a53ba8,0x34cb3ba2,0x323e3bd9,0x39fb3950,0xb78bbb0e,0xbbf8ada6,0xbaa7b872,0xbb3336fc,0x3ba834a5,0x3767bb18,0x3bd9b23e,0xab89bbfc,
    0x38f4ba48,0x3720bb2a,0x2d05bbfa,0xb1a0bbe0,0x3a4838f4,0x3bfb2c65,0x3bfa2d05,0x3abdb850,0xb8f43a48,0x35183b95,0xad053bfa,0x3a903893,
    0xba48b8f4,0xba083941,0xbbfaad05,0xb2dc3bd0,0x340abbbe,0x2a48bbfe,0xb6b3bb44,0xb913ba2f,0x3ae7b80c,0x36d7bb3b,0x358abb81,0xb4a5bba8,
    0x3bbe340a,0x39edb95f,0x3b44b6b3,0x2e46bbf6,0x380c3ae7,0x3b88b564,0x3b81358a,0x378bbb0e,0x3c00,0x34cb3ba2,0x3c00,0x358a3b81,
    0x3c00,0x39233a22,0x3c00,0x396e39e0,0x3c00,0x3b183767,0x3c00,0x3b4436b3,0x3c00,0x3bf82da6,0x3c00,0x3bfe2906,
    0x38933a90,0x3a5538e4,0x39323a15,0x3afb37d1,0x3be031a0,0x3af1b7f4,0x3bfa2d05,0x3a48b8f4,0x3a90b893,0xb013bbef,0x3a15b932,0xb458bbb3,
    0x31a0bbe0,0xbbb8b431,0x2d05bbfa,0xbbf2af86,0x3b81358a,0x3bfe2a48,0x3be73102,0x3bd9b23e,0x358abb81,0xb564bb88,0x3102bbe7,0xb872baa7,
    0xbb81b58a,0xb9ed395f,0xbbe7b102,0xb8723aa7,0xb58a3b81,0x3b3b36d7,0xb1023be7,0x3bd9323e,0x3bbeb40a,0x3ac8b83f,0x3ad2b82e,0x38f4ba48,
    0xbae7b80c,0xbbe43151,0xbbc7b378,0xbafb37d1,0x340a3bbe,0x3bcc332a,0x382e3ad2,0x3bf2af86,0x380cbae7,0xba85b8a3,0x3378bbc7,0xbbb3b458,
    0x3932ba15,0x3645bb5c,0x34f2bb9c,0xa906bbfe,0xb9323a15,0xa1073c00,0xb4f23b9c,0x36b33b44,0x3932ba15,0xb5fabb6c,0x34f2bb9c,0xb9e0b96e,
    0xb9323a15,0x399a39b6,0xb4f23b9c,0x3b81358a,0x2e46bbf6,0xb28dbbd5,0xb61fbb64,0xb96eb9e0,0x39133a2f,0x3bdc31ef,0x3b64361f,0x3b81b58a,
    0xbbf6ae46,0xb8613ab2,0xbb64361f,0xa9063bfe,0x3a2fb913,0xb882ba9c,0x361fbb64,0xbb44b6b3,0xb7d1bafb,0xb9d2b97d,0xbb21b744,0xbbf2af86,
    0x3afbb7d1,0x35afbb7a,0x3744bb21,0xb458bbb3,0x37d13afb,0x3bffa78a,0x3b213744,0x3a48b8f4,0xbafb37d1,0x368e3b4c,0xb7443b21,0x3afb37d1,
    0xbb33b6fc,0xbbeab0b2,0xbbc73378,0xbaa73872,0xb53ebb8f,0xbaddb81d,0xbad2b82e,0xbbd9323e,0x36fcbb33,0xb8c4ba6d,0xb378bbc7,0xbbd9b23e,
    0x3b8fb53e,0xb3c6bbc3,0x382ebad2,0xbaa7b872,0x3c00,0x25073c00,0x3c00,0x2c653bfb,0x3c00,0x36693b54,0x3c00,0x37203b2a,
    0x3c00,0x39c4398b,0x3c00,0x3a083941,0x3c00,0x3b7335d5,0x3c00,0x3b953518,0x29063bfe,0x2b893bfc,0x30623bed,0x328d3bd5,
    0x39e0396e,0x3b8f353e,0x3a6138d4,0x3bdc31ef,0x3bfea906,0x3950b9fb,0x3bedb062,0x3861bab2,0x396eb9e0,0xb6fcbb33,0x38d4ba61,0xb882ba9c,
    0x2d053bfa,0x2e463bf6,0x34583bb3,0x35643b88,0x3bfaad05,0x3b0eb78b,0x3bb3b458,0x39edb95f,0xad05bbfa,0xba2fb913,0xb458bbb3,0xbb3bb6d7,
    0xbbfa2d05,0xb4a53ba8,0xbbb33458,0xaa483bfe,0x2f863bf2,0x30623bed,0x36693b54,0x37673b18,0x38f4ba48,0x340abbbe,0x35d5bb73,0xada6bbf8,
    0xbbf22f86,0xb8d43a61,0xbb543669,0xb4cb3ba2,0x3a4838f4,0x3ae7b80c,0x3b7335d5,0x3923ba22,0x31023be7,0x31a03be0,0x382e3ad2,0x38a33a85,
    0xb102bbe7,0xb850babd,0xb82ebad2,0xbac8b83f,0x31023be7,0x3a903893,0x382e3ad2,0x3be43151,0xb102bbe7,0xbbd0b2dc,0xb82ebad2,0xbbcc332a,
    0x323e3bd9,0x32dc3bd0,0x39133a2f,0x397d39d2,0xbaa7b872,0xbbe0b1a0,0xbbf6ae46,0xbb7a35af,0x3bd9b23e,0x3850babd,0x3a2fb913,0x278abbff,
    0xb8723aa7,0x38933a90,0xae463bf6,0x3b4c368e,0x33783bc7,0x340a3bbe,0x39e0396e,0x3a3c3904,0xbbc73378,0xba6138d4,0xb96e39e0,0xb47e3bae,
    0xb378bbc7,0xbae7b80c,0xb9e0b96e,0xbbf42ee6,0x3bc7b378,0x3062bbed,0x396eb9e0,0xb7aebb05,0x34583bb3,0x34a53ba8,0x3a903893,0x3add381d,
    0xb7d13afb,0xae463bf6,0x31a03be0,0x38c43a6d,0xbbb33458,0xb78b3b0e,0xb8933a90,0x33c63bc3,0xbafbb7d1,0xba2f3913,0xbbe031a0,0xb0b23bea,
    0x3c00,0x2f863bf2,0x3c00,0x31513be4,0x3c00,0x37d13afb,0x3c00,0x383f3ac8,0x3c00,0x3a4838f4,0x3c00,0x3a8538a3,
    0x3c00,0x3bb33458,0x3c00,0x3bcc332a,0x33783bc7,0x358a3b81,0x353e3b8f,0x37ae3b05,0x3ad2382e,0x3bfe2906,0x3b3336fc,0x3bf4aee6,
    0x3bc7b378,0x36b3bb44,0x3b8fb53e,0x347ebbae,0x382ebad2,0xb96eb9e0,0x36fcbb33,0xba3cb904,0x37443b21,0x38723aa7,0x38f43a48,0x39ed395f,
    0x3b21b744,0x3872baa7,0x3a48b8f4,0x3564bb88,0xb744bb21,0xbbd9b23e,0xb8f4ba48,0xbbfe2a48,0xbb213744,0x323e3bd9,0xba4838f4,0x36d73b3b,
    0x39323a15,0x39e0396e,0x3abd3850,0x3b5c3645,0x2d05bbfa,0xb6b3bb44,0xb2dcbbd0,0xb99ab9b6,0xba153932,0x29063bfe,0xb8503abd,0x35fa3b6c,
    0x3bfa2d05,0x358abb81,0x3bd0b2dc,0x2107bc00,0x3a7938b4,0x3afb37d1,0x3bc73378,0x3bfb2c65,0xba79b8b4,0xbbf2af86,0xbbc7b378,0xbb953518,
    0x3a7938b4,0x3bb3b458,0x3bc73378,0x3a08b941,0xba79b8b4,0xba4838f4,0xbbc7b378,0xb7203b2a,0x3b64361f,0x3bb33458,0x3bf6ae46,0x3bb8b431,
    0xbb64361f,0xb8f43a48,0xb9133a2f,0xb0133bef,0x361fbb64,0xb7d1bafb,0xae46bbf6,0xbaf1b7f4,0x361f3b64,0x3bf2af86,0x3a2f3913,0x3a55b8e4,
    0x3be73102,0x3bfe2906,0x3b44b6b3,0x3a9cb882,0xb1023be7,0x358a3b81,0x36b33b44,0x3ab23861,0xbbe7b102,0xb9e0396e,0xbb4436b3,0xb1ef3bdc,
    0x3102bbe7,0xbb44b6b3,0xb6b3bb44,0xbbd5328d,0x3bfaad05,0x3bd9b23e,0x39c4b98b,0x38c4ba6d,0x3a153932,0x3bd9323e,0x3c002507,0x3addb81d,
    0x2d053bfa,0x3aa73872,0x398b39c4,0x3beab0b2,0xb9323a15,0x38723aa7,0xa5073c00,0x3bc333c6,0x3c00,0x32dc3bd0,0x3c00,0x34313bb8,
    0x3c00,0x38933a90,0x3c00,0x38e43a55,0x3c00,0x3abd3850,0x3c00,0x3af137f4,0x3c00,0x3be031a0,0x3c00,0x3bef3013,
    0x36b33b44,0x38d43a61,0x380c3ae7,0x39b6399a,0x3b81358a,0x3bbeb40a,0x3bbe340a,0x3b5cb645,0x3b44b6b3,0x3062bbed,0x3ae7b80c,0xa107bc00,
    0x358abb81,0xbae7b80c,0x340abbbe,0xbb6cb5fa,0x3a153932,0x3b0e378b,0x3afb37d1,0x3bc333c6,0x3932ba15,0x2e46bbf6,0x37d1bafb,0xb0b2bbea,
    0xba15b932,0xbba834a5,0xbafbb7d1,0xbadd381d,0xb9323a15,0x39133a2f,0xb7d13afb,0x3a6d38c4,0x3bb33458,0x3bfc2b89,0x3c00a507,0x3baeb47e,
    0xb7d1bafb,0xbb33b6fc,0xb9c4b98b,0xbbf4aee6,0xb4583bb3,0x395039fb,0x25073c00,0x3b0537ae,0x3afbb7d1,0xb53ebb8f,0x398bb9c4,0xb904ba3c,
    0x3be7b102,0x3b73b5d5,0x3ad2b82e,0x397db9d2,0xbbe73102,0xb9c4398b,0xbad2382e,0xb5af3b7a,0x3be7b102,0x3669bb54,0x3ad2b82e,0xa78abbff,
    0xbbe73102,0xa5073c00,0xbad2382e,0x368e3b4c,0x3aa7b872,0x398bb9c4,0x378bbb0e,0x332abbcc,0xb23e3bd9,0x36693b54,0x34a53ba8,0x3a8538a3,
    0xb872baa7,0xbc002507,0xbb0eb78b,0xbac8383f,0x3bd9323e,0x35d5bb73,0x3ba8b4a5,0xb151bbe4,0x382ebad2,0x353ebb8f,0xa906bbfe,0xb4cbbba2,
    0x3ad2382e,0x3bfcab89,0x3bfea906,0x3a22b923,0xb82e3ad2,0x36fc3b33,0x29063bfe,0x3b183767,0xbad2b82e,0xb95039fb,0xbbfe2906,0xada63bf8,
    0x2f86bbf2,0xae46bbf6,0xb850babd,0xb9edb95f,0x3a48b8f4,0x34a5bba8,0x32dcbbd0,0xb6d7bb3b,0x3bf22f86,0x3913ba2f,0x3abdb850,0xaa48bbfe,
    0x38f43a48,0x3b0eb78b,0x3bd032dc,0x3564bb88,0x3c00,0x34f23b9c,0x3c00,0x35af3b7a,0x3c00,0x39323a15,0x3c00,0x397d39d2,
    0x3c00,0x3b213744,0x3c00,0x3b4c368e,0x3c00,0x3bfa2d05,0x3c00,0x3bff278a,0x38b43a79,0x3a7938b4,0x395039fb,0x3b183767,
    0x3be73102,0x3ad2b82e,0x3bfc2b89,0x3a22b923,0x3a79b8b4,0xb102bbe7,0x39fbb950,0xb4cbbba2,0x3102bbe7,0xbbc7b378,0x2b89bbfc,0xbbf8ada6,
    0x3b9c34f2,0x3c000000,0x3bf22f86,0x3bc3b3c6,0x34f2bb9c,0xb61fbb64,0x2f86bbf2,0xb8c4ba6d,0xbb9cb4f2,0xb9a839a8,0xbbf2af86,0xb81d3add,
    0xb4f23b9c,0x3b64361f,0xaf863bf2,0x3bea30b2,0x3b9cb4f2,0x3a79b8b4,0x3a90b893,0x3882ba9c,0xbb21b744,0xbbc73378,0xbbe0b1a0,0xbab23861,
    0x34f23b9c,0x3be73102,0x38933a90,0x3bdcb1ef,0x3744bb21,0xbad2b82e,0x31a0bbe0,0xbbd5b28d,0x38b4ba79,0x34f2bb9c,0x3378bbc7,0xb013bbef,
    0xb8b43a79,0x2d053bfa,0xb3783bc7,0x37f43af1,0x38b4ba79,0xb744bb21,0x3378bbc7,0xba55b8e4,0xb8b43a79,0x3a153932,0xb3783bc7,0x3bb83431,
    0xbc00,0xb4f2bb9c,0xb78bbb0e,0xba08b941,0x39a839a8,0x3bfa2d05,0x3ba834a5,0x3b2ab720,0xbc000000,0xb7443b21,0xbb0e378b,0x2c653bfb,
    0x39a8b9a8,0xb932ba15,0x34a5bba8,0xbb95b518,0xb8b4ba79,0xba79b8b4,0xbb81b58a,0xbc002107,0x3a79b8b4,0x3378bbc7,0x358abb81,0xb645bb5c,
    0x38b43a79,0x3be7b102,0x3b81358a,0x399ab9b6,0xba7938b4,0x382e3ad2,0xb58a3b81,0x3b6c35fa,0xbb9cb4f2,0xbc000000,0xbb7335d5,0xb9ed395f,
    0xb744bb21,0xbb64b61f,0xbb54b669,0xbb883564,0x34f2bb9c,0xb9a8b9a8,0xb5d5bb73,0xbbfeaa48,0x3b21b744,0xb61fbb64,0x3669bb54,0xbb3bb6d7,
    0x3c00,0x278a3bff,0x3c00,0x2d053bfa,0x3c00,0x368e3b4c,0x3c00,0x37443b21,0x3c00,0x39d2397d,0x3c00,0x3a153932,
    0x3c00,0x3b7a35af,0x3c00,0x3b9c34f2,0x2b893bfc,0x2da63bf8,0x31023be7,0x33783bc7,0x39fb3950,0x3ba234cb,0x3a7938b4,0x3be73102,
    0x3bfcab89,0x3923ba22,0x3be7b102,0x382ebad2,0x3950b9fb,0xb767bb18,0x38b4ba79,0xb8b4ba79,0x2f863bf2,0x30b23bea,0x34f23b9c,0x361f3b64,
    0x3bf2af86,0x3addb81d,0x3b9cb4f2,0x39a8b9a8,0xaf86bbf2,0xba6db8c4,0xb4f2bb9c,0xbb64b61f,0xbbf22f86,0xb3c63bc3,0xbb9c34f2,0x3c00,
    0x31a03be0,0x328d3bd5,0x37443b21,0x382e3ad2,0x3893ba90,0x31efbbdc,0x34f2bb9c,0xb102bbe7,0xbbe031a0,0xb8613ab2,0xbb213744,0xb3783bc7,
    0x3a903893,0x3a9cb882,0x3b9c34f2,0x38b4ba79,0x33783bc7,0x34313bb8,0x38b43a79,0x39323a15,0xb378bbc7,0xb8e4ba55,0xb8b4ba79,0xbb21b744,
    0x33783bc7,0x3af137f4,0x38b43a79,0x3bfa2d05,0xb378bbc7,0xbbefb013,0xb8b4ba79,0xbb9c34f2,0x34a53ba8,0x35183b95,0x39a839a8,0x3a153932,
    0xbb0eb78b,0xbbfbac65,0xbc000000,0xbb213744,0x3ba8b4a5,0x3720bb2a,0x39a8b9a8,0xad05bbfa,0xb78b3b0e,0x39413a08,0x3c00,0x3b9c34f2,
    0x358a3b81,0x35fa3b6c,0x3a7938b4,0x3ad2382e,0xbb81358a,0xb9b6399a,0xb8b43a79,0xb1023be7,0xb58abb81,0xbb5cb645,0xba79b8b4,0xbbc73378,
    0x3b81b58a,0x2107bc00,0x38b4ba79,0xb8b4ba79,0x36693b54,0x36d73b3b,0x3b213744,0x3b64361f,0xb5d53b73,0x2a483bfe,0x34f23b9c,0x39a839a8,
    0xbb543669,0xb5643b88,0xb7443b21,0x361f3b64,0xbb73b5d5,0xb95f39ed,0xbb9c34f2,0x3c00,0x3c00,0x30133bef,0x3c00,0x31a03be0,
    0x3c00,0x37f43af1,0x3c00,0x38503abd,0x3c00,0x3a5538e4,0x3c00,0x3a903893,0x3c00,0x3bb83431,0x3c00,0x3bd032dc,
    0x340a3bbe,0x35fa3b6c,0x358a3b81,0x380c3ae7,0x3ae7380c,0x3c002107,0x3b4436b3,0x3bedb062,0x3bbeb40a,0x3645bb5c,0x3b81b58a,0x340abbbe,
    0x380cbae7,0xb99ab9b6,0x36b3bb44,0xba61b8d4,0x37d13afb,0x38c43a6d,0x39323a15,0x3a2f3913,0x3afbb7d1,0x381dbadd,0x3a15b932,0x34a5bba8,
    0xb7d1bafb,0xbbeab0b2,0xb932ba15,0xbbf62e46,0xbafb37d1,0x33c63bc3,0xba153932,0x378b3b0e,0x398b39c4,0x3a3c3904,0x3afb37d1,0x3b8f353e,
    0x2507bc00,0xb7aebb05,0xb458bbb3,0xb9fbb950,0xb9c4398b,0x2ee63bf4,0xb7d13afb,0x36fc3b33,0x3c002507,0x347ebbae,0x3bb3b458,0xab89bbfc,
    0x3ad2382e,0x3b4c368e,0x3be73102,0x3c00a507,0xbad2b82e,0xbbffa78a,0xbbe7b102,0xbb543669,0x3ad2382e,0x3b7ab5af,0x3be73102,0x398bb9c4,
    0xbad2b82e,0xb9d2397d,0xbbe7b102,0xb5d53b73,0x3ba834a5,0x3be43151,0x3bd9b23e,0x3b73b5d5,0xbb0e378b,0xb83f3ac8,0xb8723aa7,0xa5073c00,
    0x34a5bba8,0xb8a3ba85,0xb23ebbd9,0xbb54b669,0x378b3b0e,0x3bccb32a,0x3aa73872,0x39c4b98b,0x3bfe2906,0x3bf8ada6,0x3ad2b82e,0x39fbb950,
    0xa9063bfe,0x37673b18,0x382e3ad2,0x3b3336fc,0xbbfea906,0xb9233a22,0xbad2382e,0xab893bfc,0x2906bbfe,0xbba2b4cb,0xb82ebad2,0xbb8f353e,
    0x3bd0b2dc,0x3b88b564,0x38f4ba48,0x378bbb0e,0x3abd3850,0x3bfe2a48,0x3bf2af86,0x3a2fb913,0x32dc3bd0,0x3b3b36d7,0x3a4838f4,0x3ba8b4a5,
    0xb8503abd,0x395f39ed,0x2f863bf2,0x3bf62e46,0x3c00,0x332a3bcc,0x3c00,0x34583bb3,0x3c00,0x38a33a85,0x3c00,0x38f43a48,
    0x3c00,0x3ac8383f,0x3c00,0x3afb37d1,0x3c00,0x3be43151,0x3c00,0x3bf22f86,0x36fc3b33,0x39043a3c,0x382e3ad2,0x39e0396e,
    0x3b8f353e,0x3baeb47e,0x3bc73378,0x3b44b6b3,0x3b33b6fc,0x2ee6bbf4,0x3ad2b82e,0xa906bbfe,0x353ebb8f,0xbb05b7ae,0x3378bbc7,0xbb81b58a,
    0x3a4838f4,0x3b3b36d7,0x3b213744,0x3bd9323e,0x38f4ba48,0x2a48bbfe,0x3744bb21,0xb23ebbd9,0xba48b8f4,0xbb883564,0xbb21b744,0xbaa73872,
    0xb8f43a48,0x395f39ed,0xb7443b21,0x3aa73872,0x3bd032dc,0x3c00a107,0x3bfaad05,0x3b81b58a,0xb850babd,0xbb6cb5fa,0xba15b932,0xbbfea906,
    0xb2dc3bd0,0x39b6399a,0x2d053bfa,0x3b4436b3,0x3abdb850,0xb645bb5c,0x3932ba15,0xb96eb9e0,0x3bc7b378,0x3b2ab720,0x3a79b8b4,0x38f4ba48,
    0xbbc73378,0xb9413a08,0xba7938b4,0xb4583bb3,0x3bc7b378,0x3518bb95,0x3a79b8b4,0xaf86bbf2,0xbbc73378,0x2c653bfb,0xba7938b4,0x37d13afb,
    0x3a2fb913,0x38e4ba55,0x361fbb64,0x2f86bbf2,0xae463bf6,0x37f43af1,0x361f3b64,0x3afb37d1,0xb913ba2f,0xbbef3013,0xbb64b61f,0xba4838f4,
    0x3bf62e46,0x3431bbb8,0x3b64b61f,0xb458bbb3,0x36b3bb44,0x328dbbd5,0xb102bbe7,0xb6b3bb44,0x3b4436b3,0x3bdcb1ef,0x3be7b102,0x396eb9e0,
    0xb6b33b44,0x38613ab2,0x31023be7,0x3b81358a,0xbb44b6b3,0xb8823a9c,0xbbe73102,0x29063bfe,0xa507bc00,0xb3c6bbc3,0xb932ba15,0xbaa7b872,
    0x398bb9c4,0x30b2bbea,0x2d05bbfa,0xb872baa7,0x3c00a507,0x381dbadd,0x3a15b932,0xb23ebbd9,0x39c4398b,0x3a6db8c4,0x3bfa2d05,0x323ebbd9,
    0x3c00,0x35183b95,0x3c00,0x35d53b73,0x3c00,0x39413a08,0x3c00,0x398b39c4,0x3c00,0x3b2a3720,0x3c00,0x3b543669,
    0x3c00,0x3bfb2c65,0x3c00,0x3c002507,0x38d43a61,0x3a9c3882,0x396e39e0,0x3b3336fc,0x3bed3062,0x3ab2b861,0x3bfe2906,0x39fbb950,
    0x3a61b8d4,0xb1efbbdc,0x39e0b96e,0xb53ebb8f,0x3062bbed,0xbbd5b28d,0x2906bbfe,0xbbfcab89,0x3bb33458,0x3bfeaa48,0x3bfa2d05,0x3ba8b4a5,
    0x3458bbb3,0xb6d7bb3b,0x2d05bbfa,0xb913ba2f,0xbbb3b458,0xb95f39ed,0xbbfaad05,0xb78b3b0e,0xb4583bb3,0x3b883564,0xad053bfa,0x3bf62e46,
    0x3b73b5d5,0x3a22b923,0x3a48b8f4,0x380cbae7,0xbb54b669,0xbba234cb,0xbbf2af86,0xba6138d4,0x35d53b73,0x3bf82da6,0x38f43a48,0x3bbeb40a,
    0x3669bb54,0xbb18b767,0x2f86bbf2,0xbbedb062,0x382ebad2,0x332abbcc,0x3102bbe7,0xb2dcbbd0,0xb82e3ad2,0x31513be4,0xb1023be7,0x38933a90,
    0x382ebad2,0xb83fbac8,0x3102bbe7,0xbabdb850,0xb82e3ad2,0x3a8538a3,0xb1023be7,0x3be031a0,0xae46bbf6,0xb68ebb4c,0xb872baa7,0xba90b893,
    0x3a2f3913,0x3bffa78a,0x3bd9323e,0x3abdb850,0xbbf62e46,0xb5af3b7a,0xbaa73872,0x31a03be0,0x3913ba2f,0xb9d2b97d,0x323ebbd9,0xbbd0b2dc,
    0xb96eb9e0,0xbb05b7ae,0xbbc7b378,0xbbed3062,0x39e0b96e,0x2ee6bbf4,0x3378bbc7,0xb80cbae7,0x396e39e0,0x3baeb47e,0x3bc73378,0x38d4ba61,
    0xb9e0396e,0x39043a3c,0xb3783bc7,0x3bbe340a,0xbbe0b1a0,0xbbea30b2,0xbafb37d1,0xb9133a2f,0xb893ba90,0xbbc3b3c6,0xbbb3b458,0xbb0e378b,
    0x31a0bbe0,0xba6db8c4,0xb7d1bafb,0xbbf62e46,0x3a90b893,0xb81dbadd,0x3458bbb3,0xbba8b4a5,0x3c00,0x29063bfe,0x3c00,0x2da63bf8,
    0x3c00,0x36b33b44,0x3c00,0x37673b18,0x3c00,0x39e0396e,0x3c00,0x3a223923,0x3c00,0x3b81358a,0x3c00,0x3ba234cb,
    0x2d053bfa,0x2f863bf2,0x31a03be0,0x34313bb8,0x3a153932,0x3bb33458,0x3a903893,0x3bef3013,0x3bfaad05,0x38f4ba48,0x3be0b1a0,0x37f4baf1,
    0x3932ba15,0xb7d1bafb,0x3893ba90,0xb8e4ba55,0x31023be7,0x323e3bd9,0x358a3b81,0x36d73b3b,0x3be7b102,0x3aa7b872,0x3b81b58a,0x395fb9ed,
    0xb102bbe7,0xbaa7b872,0xb58abb81,0xbb88b564,0xbbe73102,0xb23e3bd9,0xbb81358a,0x2a483bfe,0x33783bc7,0x34583bb3,0x380c3ae7,0x38a33a85,
    0x382ebad2,0x2f86bbf2,0x340abbbe,0xb32abbcc,0xbbc73378,0xb7d13afb,0xbae7380c,0xb1513be4,0x3ad2382e,0x3a48b8f4,0x3bbe340a,0x383fbac8,
    0x34f23b9c,0x358a3b81,0x39323a15,0x39b6399a,0xb4f2bb9c,0xb96eb9e0,0xb932ba15,0xbb6cb5fa,0x34f23b9c,0x3b4436b3,0x39323a15,0x3c00a107,
    0xb4f2bb9c,0xbbfea906,0xb932ba15,0xbb5c3645,0x361f3b64,0x36b33b44,0x3a2f3913,0x3a9c3882,0xbb64b61f,0xbbfe2906,0xbbf62e46,0xbab23861,
    0x3b64b61f,0x358abb81,0x3913ba2f,0xb1efbbdc,0xb61f3b64,0x39e0396e,0x2e463bf6,0x3bd5328d,0x37443b21,0x37d13afb,0x3afb37d1,0x3b4c368e,
    0xbb213744,0xb8f43a48,0xb7d13afb,0xa78a3bff,0xb744bb21,0xbbb3b458,0xbafbb7d1,0xbb7a35af,0x3b21b744,0xaf86bbf2,0x37d1bafb,0xb97db9d2,
    0x382e3ad2,0x38723aa7,0x3b8f353e,0x3bc333c6,0xb3783bc7,0x323e3bd9,0x36fc3b33,0x3a6d38c4,0xbad2382e,0xb23e3bd9,0xb53e3b8f,0x381d3add,
    0xbbc7b378,0xb8723aa7,0xbb3336fc,0x30b23bea,0x3c00,0x30623bed,0x3c00,0x31ef3bdc,0x3c00,0x380c3ae7,0x3c00,0x38613ab2,
    0x3c00,0x3a6138d4,0x3c00,0x3a9c3882,0x3c00,0x3bbe340a,0x3c00,0x3bd5328d,0x34583bb3,0x36693b54,0x35d53b73,0x383f3ac8,
    0x3afb37d1,0x3c00a507,0x3b543669,0x3be4b151,0x3bb3b458,0x35d5bb73,0x3b73b5d5,0x332abbcc,0x37d1bafb,0xb9c4b98b,0x3669bb54,0xba85b8a3,
    0x382e3ad2,0x39133a2f,0x396e39e0,0x3a6d38c4,0x3ad2b82e,0x378bbb0e,0x39e0b96e,0x33c6bbc3,0xb82ebad2,0xbbf6ae46,0xb96eb9e0,0xbbea30b2,
    0xbad2382e,0x34a53ba8,0xb9e0396e,0x381d3add,0x39e0396e,0x3a903893,0x3b3336fc,0x3bb83431,0xa906bbfe,0xb850babd,0xb53ebb8f,0xba55b8e4,
    0xb96e39e0,0x31a03be0,0xb6fc3b33,0x37f43af1,0x3bfea906,0x32dcbbd0,0x3b8fb53e,0xb013bbef,0x3b213744,0x3b8f353e,0x3bfa2d05,0x3bf4aee6,
    0xbb21b744,0xbbfc2b89,0xbbfaad05,0xbb0537ae,0x3b213744,0x3b33b6fc,0x3bfa2d05,0x3904ba3c,0xbb21b744,0xb95039fb,0xbbfaad05,0xb47e3bae,
    0x3bd9323e,0x3bfc2b89,0x3ba8b4a5,0x3b18b767,0xbaa73872,0xb6fc3b33,0xb78b3b0e,0x2da63bf8,0x323ebbd9,0xb950b9fb,0xb4a5bba8,0xbba2b4cb,
    0x38723aa7,0x3b8fb53e,0x3b0e378b,0x3923ba22,0x3bfaad05,0x3bd0b2dc,0x3a48b8f4,0x3941ba08,0x2d053bfa,0x38933a90,0x38f43a48,0x3b953518,
    0xbbfa2d05,0xb8503abd,0xba4838f4,0x2c653bfb,0xad05bbfa,0xbbe0b1a0,0xb8f4ba48,0xbb2a3720,0x3b81b58a,0x3b0eb78b,0x380cbae7,0x3564bb88,
    0x3b4436b3,0x3bf6ae46,0x3bbeb40a,0x395fb9ed,0x358a3b81,0x3ba834a5,0x3ae7380c,0x3b3bb6d7,0xb6b33b44,0x3a2f3913,0x340a3bbe,0x3bfeaa48,
    0x3c00,0x33783bc7,0x3c00,0x347e3bae,0x3c00,0x38b43a79,0x3c00,0x39043a3c,0x3c00,0x3ad2382e,0x3c00,0x3b0537ae,
    0x3c00,0x3be73102,0x3c00,0x3bf42ee6,0x37443b21,0x39323a15,0x38503abd,0x3a083941,0x3b9c34f2,0x3b9cb4f2,0x3bd032dc,0x3b2ab720,
    0x3b21b744,0x2d05bbfa,0x3abdb850,0xac65bbfb,0x34f2bb9c,0xbb21b744,0x32dcbbd0,0xbb95b518,0x3a7938b4,0x3b64361f,0x3b4436b3,0x3bea30b2,
    0x38b4ba79,0xbc00,0x36b3bb44,0xb3c6bbc3,0xba79b8b4,0xbb64361f,0xbb44b6b3,0xba6d38c4,0xb8b43a79,0x39a839a8,0xb6b33b44,0x3add381d,
    0x3be73102,0x3bfaad05,0x3bedb062,0x3b4cb68e,0xb8b4ba79,0xbb9cb4f2,0xba61b8d4,0xbbff278a,0xb1023be7,0x3a153932,0x30623bed,0x3b7a35af,
    0x3a79b8b4,0xb744bb21,0x38d4ba61,0xb9d2b97d,0x3b9cb4f2,0x3ad2b82e,0x3a15b932,0x3861bab2,0xbb9c34f2,0xb8b43a79,0xba153932,0xb1ef3bdc,
    0x3b9cb4f2,0x3378bbc7,0x3a15b932,0xb28dbbd5,0xbb9c34f2,0x31023be7,0xba153932,0x38823a9c,0x39a8b9a8,0x382ebad2,0x34a5bba8,0x2107bc00,
    0x3c00,0x38b43a79,0x378b3b0e,0x3b5c3645,0xb9a8b9a8,0xbbc73378,0xbba8b4a5,0xb9b6399a,0x3c000000,0x3102bbe7,0x3b0eb78b,0xb5fabb6c,
    0x34f2bb9c,0x2d05bbfa,0xb458bbb3,0xb83fbac8,0x3b9c34f2,0x3b9cb4f2,0x3bb3b458,0x38a3ba85,0xb4f23b9c,0x39323a15,0x34583bb3,0x3bcc332a,
    0xbb9cb4f2,0xb7443b21,0xbbb33458,0x31513be4,0xb102bbe7,0xb61fbb64,0xb9fbb950,0xbb3bb6d7,0x38b4ba79,0xbc00,0xab89bbfc,0xb95fb9ed,
    0x3be7b102,0x361fbb64,0x3950b9fb,0xb564bb88,0x3a7938b4,0x39a8b9a8,0x3bfcab89,0x2a48bbfe,0x3c00,0x353e3b8f,0x3c00,0x35fa3b6c,
    0x3c00,0x395039fb,0x3c00,0x399a39b6,0x3c00,0x3b3336fc,0x3c00,0x3b5c3645,0x3c00,0x3bfc2b89,0x3c00,0x3c002107,
    0x38f43a48,0x3abd3850,0x398b39c4,0x3b4c368e,0x3bf22f86,0x3a90b893,0x3c002507,0x39d2b97d,0x3a48b8f4,0xb2dcbbd0,0x39c4b98b,0xb5afbb7a,
    0x2f86bbf2,0xbbe0b1a0,0x2507bc00,0xbbffa78a,0x3bc73378,0x3bf6ae46,0x3bfe2906,0x3b88b564,0x3378bbc7,0xb78bbb0e,0x2906bbfe,0xb95fb9ed,
    0xbbc7b378,0xb9133a2f,0xbbfea906,0xb6d73b3b,0xb3783bc7,0x3ba834a5,0xa9063bfe,0x3bfe2a48,0x3b44b6b3,0x39c4b98b,0x39fbb950,0x3720bb2a,
    0xbb81b58a,0xbb7335d5,0xbbfcab89,0xba083941,0x36b33b44,0x3c002507,0x395039fb,0x3b95b518,0x358abb81,0xbb54b669,0x2b89bbfc,0xbbfbac65,
    0x3744bb21,0x3062bbed,0x2d05bbfa,0xb4cbbba2,0xb7443b21,0x340a3bbe,0xad053bfa,0x39233a22,0x3744bb21,0xb8d4ba61,0x2d05bbfa,0xbb18b767,
    0xb7443b21,0x3ae7380c,0xad053bfa,0x3bf82da6,0xb23ebbd9,0xb80cbae7,0xb913ba2f,0xbb05b7ae,0x3aa73872,0x3bedb062,0x3bf62e46,0x3a3cb904,
    0xbbd9323e,0xb40a3bbe,0xba2f3913,0x347e3bae,0x3872baa7,0xba61b8d4,0x2e46bbf6,0xbbf4aee6,0xba15b932,0xbb73b5d5,0xbbf2af86,0xbbb83431,
    0x3932ba15,0xa507bc00,0x2f86bbf2,0xb8e4ba55,0x3a153932,0x3b54b669,0x3bf22f86,0x37f4baf1,0xb9323a15,0x39c4398b,0xaf863bf2,0x3bef3013,
    0xbbfea906,0xbba834a5,0xba6138d4,0xb81d3add,0xb96eb9e0,0xbbf6ae46,0xbbedb062,0xba6d38c4,0x2906bbfe,0xbb0eb78b,0xb8d4ba61,0xbbc333c6,
    0x39e0b96e,0xb913ba2f,0x3062bbed,0xbbeab0b2,
};

#define TS(i, cond)
#define TW(i)
#define TV(i, v)
#define TC(i, cond)
__device__ __forceinline__ float bf_lo(uint32_t v) { return __uint_as_float(v << 16); }
__device__ __forceinline__ float bf_hi(uint32_t v) { return __uint_as_float(v & 0xffff0000u); }
__device__ __forceinline__ uint32_t pack_bf2(float lo, float hi) {
    uint32_t r;
    asm("cvt.rn.bf16x2.f32 %0, %1, %2;" : "=r"(r) : "f"(hi), "f"(lo));
    return r;
}
__device__ __forceinline__ float bf_round(float v) { return __uint_as_float(pack_bf2(0.f, v)); }
__device__ __forceinline__ void split2(float a, float b, uint32_t& hi, uint32_t& lo) {
    hi = pack_bf2(a, b);
    lo = pack_bf2(a - bf_lo(hi), b - bf_hi(hi));
}
__device__ __forceinline__ uint32_t hsub2(uint32_t a, uint32_t b) {
    uint32_t r;
    asm("sub.rn.bf16x2 %0, %1, %2;" : "=r"(r) : "r"(a), "r"(b));
    return r;
}
__device__ __forceinline__ uint32_t hadd2(uint32_t a, uint32_t b) {
    uint32_t r;
    asm("add.rn.bf16x2 %0, %1, %2;" : "=r"(r) : "r"(a), "r"(b));
    return r;
}
__device__ __forceinline__ uint32_t hmul2(uint32_t a, uint32_t b) {
    uint32_t r;
    asm("mul.rn.bf16x2 %0, %1, %2;" : "=r"(r) : "r"(a), "r"(b));
    return r;
}
__device__ __forceinline__ uint32_t hfma2(uint32_t a, uint32_t b, uint32_t c) {
    uint32_t r;
    asm("fma.rn.bf16x2 %0, %1, %2, %3;" : "=r"(r) : "r"(a), "r"(b), "r"(c));
    return r;
}
__device__ __forceinline__ uint32_t dup_lo(uint32_t v) { return __byte_perm(v, 0, 0x1010); }
__device__ __forceinline__ uint32_t ldg_nc32(const void* p) {
    uint32_t r;
    asm volatile("ld.global.nc.L1::no_allocate.b32 %0, [%1];" : "=r"(r) : "l"(p));
    return r;
}
__device__ __forceinline__ uint32_t ldg_nc16(const void* p) {
    unsigned short r;
    asm volatile("ld.global.nc.b16 %0, [%1];" : "=h"(r) : "l"(p));
    return (uint32_t)r;
}
__device__ __forceinline__ void cp_async16(uint32_t dst, const void* src) {
    asm volatile("cp.async.cg.shared.global [%0], [%1], 16;" ::"r"(dst), "l"(src) : "memory");
}
__device__ __forceinline__ void cp_async_wait_all() { asm volatile("cp.async.wait_all;" ::: "memory"); }
__device__ __forceinline__ void ldsm4(uint32_t* a, uint32_t addr) {
    asm volatile("ldmatrix.sync.aligned.m8n8.x4.shared.b16 {%0,%1,%2,%3}, [%4];"
                 : "=r"(a[0]), "=r"(a[1]), "=r"(a[2]), "=r"(a[3]) : "r"(addr));
}
__device__ __forceinline__ void ldsm4t(uint32_t* a, uint32_t addr) {
    asm volatile("ldmatrix.sync.aligned.m8n8.x4.trans.shared.b16 {%0,%1,%2,%3}, [%4];"
                 : "=r"(a[0]), "=r"(a[1]), "=r"(a[2]), "=r"(a[3]) : "r"(addr));
}
__device__ __forceinline__ void stsm4(uint32_t addr, const uint32_t* a) {
    asm volatile("stmatrix.sync.aligned.m8n8.x4.shared.b16 [%0], {%1,%2,%3,%4};"
                 ::"r"(addr), "r"(a[0]), "r"(a[1]), "r"(a[2]), "r"(a[3]) : "memory");
}
__device__ __forceinline__ void mma_acc(float* d, const uint32_t* a, uint32_t b0, uint32_t b1) {
    asm("mma.sync.aligned.m16n8k16.row.col.f32.bf16.bf16.f32 {%0,%1,%2,%3}, {%4,%5,%6,%7}, {%8,%9}, {%0,%1,%2,%3};"
        : "+f"(d[0]), "+f"(d[1]), "+f"(d[2]), "+f"(d[3])
        : "r"(a[0]), "r"(a[1]), "r"(a[2]), "r"(a[3]), "r"(b0), "r"(b1));
}
__device__ __forceinline__ void mma_k8(float* d, uint32_t a0, uint32_t a1, uint32_t b) {
    asm volatile("mma.sync.aligned.m16n8k8.row.col.f32.bf16.bf16.f32 {%0,%1,%2,%3}, {%4,%5}, {%6}, {%0,%1,%2,%3};"
                 : "+f"(d[0]), "+f"(d[1]), "+f"(d[2]), "+f"(d[3]) : "r"(a0), "r"(a1), "r"(b));
}
__device__ __forceinline__ void mma_zero(float* d, const uint32_t* a, uint32_t b0, uint32_t b1) {
    asm("mma.sync.aligned.m16n8k16.row.col.f32.bf16.bf16.f32 {%0,%1,%2,%3}, {%4,%5,%6,%7}, {%8,%9}, {%10,%10,%10,%10};"
        : "=f"(d[0]), "=f"(d[1]), "=f"(d[2]), "=f"(d[3])
        : "r"(a[0]), "r"(a[1]), "r"(a[2]), "r"(a[3]), "r"(b0), "r"(b1), "f"(0.f));
}
__device__ __forceinline__ void mma_h(float* d, uint32_t a0, uint32_t a1, uint32_t a2, uint32_t a3, uint32_t b0, uint32_t b1) {
    asm("mma.sync.aligned.m16n8k16.row.col.f32.f16.f16.f32 {%0,%1,%2,%3}, {%4,%5,%6,%7}, {%8,%9}, {%0,%1,%2,%3};"
        : "+f"(d[0]), "+f"(d[1]), "+f"(d[2]), "+f"(d[3])
        : "r"(a0), "r"(a1), "r"(a2), "r"(a3), "r"(b0), "r"(b1));
}
__device__ __forceinline__ void mma_h0(float* d, uint32_t a0, uint32_t a1, uint32_t a2, uint32_t a3, uint32_t b0, uint32_t b1) {
    asm("mma.sync.aligned.m16n8k16.row.col.f32.f16.f16.f32 {%0,%1,%2,%3}, {%4,%5,%6,%7}, {%8,%9}, {%10,%10,%10,%10};"
        : "=f"(d[0]), "=f"(d[1]), "=f"(d[2]), "=f"(d[3])
        : "r"(a0), "r"(a1), "r"(a2), "r"(a3), "r"(b0), "r"(b1), "f"(0.f));
}
__device__ __forceinline__ void mma_g(uint32_t* d, uint32_t a0, uint32_t a1, uint32_t a2, uint32_t a3, uint32_t b0, uint32_t b1) {
    asm("mma.sync.aligned.m16n8k16.row.col.f16.f16.f16.f16 {%0,%1}, {%2,%3,%4,%5}, {%6,%7}, {%0,%1};"
        : "+r"(d[0]), "+r"(d[1]) : "r"(a0), "r"(a1), "r"(a2), "r"(a3), "r"(b0), "r"(b1));
}
__device__ __forceinline__ void mma_g0(uint32_t* d, uint32_t a0, uint32_t a1, uint32_t a2, uint32_t a3, uint32_t b0, uint32_t b1) {
    asm("mma.sync.aligned.m16n8k16.row.col.f16.f16.f16.f16 {%0,%1}, {%2,%3,%4,%5}, {%6,%7}, {%8,%8};"
        : "=r"(d[0]), "=r"(d[1]) : "r"(a0), "r"(a1), "r"(a2), "r"(a3), "r"(b0), "r"(b1), "r"(0));
}
__device__ __forceinline__ uint32_t movm(uint32_t a) {
    uint32_t r;
    asm("movmatrix.sync.aligned.m8n8.trans.b16 %0, %1;" : "=r"(r) : "r"(a));
    return r;
}
__device__ __forceinline__ uint32_t pack_h2(float lo, float hi) {
    uint32_t r;
    asm("cvt.rn.f16x2.f32 %0, %1, %2;" : "=r"(r) : "f"(hi), "f"(lo));
    return r;
}
__device__ __forceinline__ uint32_t fmul2(uint32_t a, uint32_t b) {
    uint32_t r;
    asm("mul.rn.f16x2 %0, %1, %2;" : "=r"(r) : "r"(a), "r"(b));
    return r;
}
__device__ __forceinline__ uint32_t lds4(uint32_t a) {
    uint32_t r;
    asm volatile("ld.shared.b32 %0, [%1];" : "=r"(r) : "r"(a) : "memory");
    return r;
}
__device__ __forceinline__ uint32_t fadd2(uint32_t a, uint32_t b) {
    uint32_t r;
    asm("add.rn.f16x2 %0, %1, %2;" : "=r"(r) : "r"(a), "r"(b));
    return r;
}
__device__ __forceinline__ uint32_t fsub2(uint32_t a, uint32_t b) {
    uint32_t r;
    asm("sub.rn.f16x2 %0, %1, %2;" : "=r"(r) : "r"(a), "r"(b));
    return r;
}
__device__ __forceinline__ uint32_t ffma2(uint32_t a, uint32_t b, uint32_t c) {
    uint32_t r;
    asm("fma.rn.f16x2 %0, %1, %2, %3;" : "=r"(r) : "r"(a), "r"(b), "r"(c));
    return r;
}
__device__ __forceinline__ uint32_t fms2(uint32_t a, uint32_t b, uint32_t c, uint32_t d) {
    uint32_t r;
    asm("{\n.reg .b32 t;\nmul.rn.f16x2 t, %3, %4;\nneg.f16x2 t, t;\nfma.rn.f16x2 %0, %1, %2, t;\n}\n" : "=r"(r) : "r"(a), "r"(b), "r"(c), "r"(d));
    return r;
}
__device__ __forceinline__ uint32_t fmp2(uint32_t a, uint32_t b, uint32_t c, uint32_t d) { return ffma2(a, b, fmul2(c, d)); }
__device__ __forceinline__ uint32_t or3(uint32_t a, uint32_t b, uint32_t c) {
    uint32_t r;
    asm("lop3.b32 %0, %1, %2, %3, 0xfe;" : "=r"(r) : "r"(a), "r"(b), "r"(c));
    return r;
}
__device__ __forceinline__ uint32_t m640(uint32_t x) {
    x = min(x, x - 1280u);
    return min(x, x - 640u);
}
#define BAR_SYNC(id, n) asm volatile("bar.sync %0, %1;" ::"n"(id), "n"(n) : "memory")
#define BAR_ARRIVE(id, n) asm volatile("bar.arrive %0, %1;" ::"n"(id), "n"(n) : "memory")

__device__ __forceinline__ float2 cadd(float2 a, float2 b) { return make_float2(a.x + b.x, a.y + b.y); }
__device__ __forceinline__ float2 csub(float2 a, float2 b) { return make_float2(a.x - b.x, a.y - b.y); }
__device__ __forceinline__ void dft5(uint32_t* x) {
    const uint32_t c1 = 0x34f234f2u, c2 = 0xba79ba79u;
    const uint32_t s1 = 0xbb9c3b9cu, s2 = 0xb8b438b4u;
    const uint32_t t1 = fadd2(x[1], x[4]), t2 = fadd2(x[2], x[3]);
    const uint32_t t3 = __byte_perm(fsub2(x[1], x[4]), 0, 0x1032), t4 = __byte_perm(fsub2(x[2], x[3]), 0, 0x1032);
    const uint32_t a1 = ffma2(c2, t2, ffma2(c1, t1, x[0])), a2 = ffma2(c1, t2, ffma2(c2, t1, x[0]));
    const uint32_t b1 = fmp2(s1, t3, s2, t4), b2 = fms2(s2, t3, s1, t4);
    x[0] = fadd2(fadd2(x[0], t1), t2);
    x[1] = fadd2(a1, b1);
    x[4] = fsub2(a1, b1);
    x[2] = fadd2(a2, b2);
    x[3] = fsub2(a2, b2);
}
#define SPIN_LIMIT (1 << 16)
__device__ __forceinline__ void wg_fence() { asm volatile("wgmma.fence.sync.aligned;" ::: "memory"); }
__device__ __forceinline__ void wg_commit() { asm volatile("wgmma.commit_group.sync.aligned;" ::: "memory"); }
template <int N>
__device__ __forceinline__ void wg_wait() { asm volatile("wgmma.wait_group.sync.aligned %0;" ::"n"(N) : "memory"); }

__device__ __forceinline__ uint32_t smem_u32(const void* p) { return (uint32_t)__cvta_generic_to_shared(p); }
__device__ __forceinline__ void mbar_init(uint32_t bar, uint32_t count) {
    asm volatile("mbarrier.init.shared::cta.b64 [%0], %1;" ::"r"(bar), "r"(count) : "memory");
}
__device__ __forceinline__ void mbar_arrive(uint32_t bar) {
    asm volatile("mbarrier.arrive.shared::cta.b64 _, [%0];" ::"r"(bar) : "memory");
}
__device__ __forceinline__ void mbar_expect_tx(uint32_t bar, uint32_t bytes) {
    asm volatile("mbarrier.arrive.expect_tx.shared::cta.b64 _, [%0], %1;" ::"r"(bar), "r"(bytes) : "memory");
}
__device__ __forceinline__ void mbar_wait(uint32_t bar, uint32_t parity) {
    asm volatile(
        "{\n.reg .pred p;\n.reg .u32 c;\n"
        "mov.u32 c, 0;\n"
        "W_%=:\n"
        "mbarrier.try_wait.parity.shared::cta.b64 p, [%0], %1;\n"
        "@p bra D_%=;\n"
        "add.u32 c, c, 1;\n"
        "setp.lt.u32 p, c, 16384;\n"
        "@p bra W_%=;\n"
        "D_%=:\n}\n" ::"r"(bar), "r"(parity) : "memory");
}
__device__ __forceinline__ void mbar_arrive_cl(uint32_t bar) {
    asm volatile("mbarrier.arrive.relaxed.cluster.shared::cluster.b64 _, [%0];" ::"r"(bar) : "memory");
}
__device__ __forceinline__ uint32_t mapa(uint32_t a, uint32_t rank) {
    uint32_t r;
    asm("mapa.shared::cluster.u32 %0, %1, %2;" : "=r"(r) : "r"(a), "r"(rank));
    return r;
}
__device__ __forceinline__ void st_async16(uint32_t dst, const uint32_t* a, uint32_t bar) {
    asm volatile("st.async.weak.shared::cluster.mbarrier::complete_tx::bytes.v4.b32 [%0], {%1,%2,%3,%4}, [%5];"
                 ::"r"(dst), "r"(a[0]), "r"(a[1]), "r"(a[2]), "r"(a[3]), "r"(bar) : "memory");
}
__device__ __forceinline__ void lds16(uint32_t* a, uint32_t src) {
    asm volatile("ld.shared.v4.b32 {%0,%1,%2,%3}, [%4];"
                 : "=r"(a[0]), "=r"(a[1]), "=r"(a[2]), "=r"(a[3]) : "r"(src) : "memory");
}
__device__ __forceinline__ void tma_load3(uint32_t dst, const CUtensorMap* tm, int c1, int c2, uint32_t bar) {
    asm volatile(
        "cp.async.bulk.tensor.3d.shared::cluster.global.mbarrier::complete_tx::bytes [%0], [%1, {%2, %3, %4}], [%5];"
        ::"r"(dst), "l"(tm), "r"(0), "r"(c1), "r"(c2), "r"(bar) : "memory");
}
__device__ __forceinline__ void l2_prefetch(const void* p, uint32_t bytes) {
    asm volatile("cp.async.bulk.prefetch.L2.global [%0], %1;" ::"l"(p), "r"(bytes) : "memory");
}
__device__ __forceinline__ float ex2f(float v) { float r; asm("ex2.approx.ftz.f32 %0, %1;" : "=f"(r) : "f"(v)); return r; }
__device__ __forceinline__ float rcpf(float v) { float r; asm("rcp.approx.ftz.f32 %0, %1;" : "=f"(r) : "f"(v)); return r; }
__device__ __forceinline__ float sqrtf_a(float v) { float r; asm("sqrt.approx.ftz.f32 %0, %1;" : "=f"(r) : "f"(v)); return r; }
__device__ __forceinline__ float silu1(float v) { return v * rcpf(1.f + ex2f(v * -1.4426950408889634f)); }
__device__ __forceinline__ void silu4(const float* d, uint32_t& o0, uint32_t& o1) {
    o0 = pack_bf2(silu1(d[0]), silu1(d[1]));
    o1 = pack_bf2(silu1(d[2]), silu1(d[3]));
}

__device__ __forceinline__ uint32_t ld_rlx32(const uint32_t* p) {
    uint32_t r;
    asm volatile("ld.relaxed.gpu.global.b32 %0, [%1];" : "=r"(r) : "l"(p) : "memory");
    return r;
}
__device__ __forceinline__ void st_rlx32(uint32_t* p, uint32_t v) {
    asm volatile("st.relaxed.gpu.global.b32 [%0], %1;" ::"l"(p), "r"(v) : "memory");
}
__device__ __forceinline__ uint32_t pack_h2z(float lo, float hi) {
    uint32_t r;
    asm("cvt.rz.f16x2.f32 %0, %1, %2;" : "=r"(r) : "f"(hi), "f"(lo));
    return r;
}
__device__ __forceinline__ float2 unpack_h2(uint32_t v) {
    float2 r;
    asm("{\n.reg .b16 l, h;\nmov.b32 {l, h}, %2;\ncvt.f32.f16 %0, l;\ncvt.f32.f16 %1, h;\n}\n" : "=f"(r.x), "=f"(r.y) : "r"(v));
    return r;
}
__device__ __forceinline__ float pow2i(int e) { return __int_as_float((e + 127) << 23); }
__device__ __forceinline__ uint32_t warp_max16(uint32_t m) { return __reduce_max_sync(0xffffffffu, max(m & 0xffffu, m >> 16)); }
__device__ __forceinline__ void st_rlx64(void* p, uint32_t lo, uint32_t hi) {
    unsigned long long v = (unsigned long long)lo | ((unsigned long long)hi << 32);
    asm volatile("st.relaxed.gpu.global.b64 [%0], %1;" ::"l"(p), "l"(v) : "memory");
}
__device__ __forceinline__ uint4 ld_rlx128(const void* p) {
    uint4 r;
    asm volatile("{\n.reg .b128 t;\nld.relaxed.gpu.global.b128 t, [%4];\nmov.b128 {%0,%1,%2,%3}, t;\n}\n"
                 : "=r"(r.x), "=r"(r.y), "=r"(r.z), "=r"(r.w) : "l"(p) : "memory");
    return r;
}
__device__ __forceinline__ void st_rlx128(uint4* p, uint32_t a, uint32_t b, uint32_t c, uint32_t d) {
    asm volatile("{\n.reg .b128 t;\nmov.b128 t, {%1,%2,%3,%4};\nst.relaxed.gpu.global.b128 [%0], t;\n}\n"
                 ::"l"(p), "r"(a), "r"(b), "r"(c), "r"(d) : "memory");
}
__device__ __forceinline__ void red_add(unsigned int* p) {
    asm volatile("red.relaxed.gpu.global.add.u32 [%0], 1;" ::"l"(p) : "memory");
}
__device__ __forceinline__ void hint_wait(const unsigned int* p, uint32_t target) {
#pragma unroll 1
    for (int it = 0; it < SPIN_LIMIT; it++) {
        uint32_t v;
        asm volatile("ld.relaxed.gpu.global.u32 %0, [%1];" : "=r"(v) : "l"(p) : "memory");
        if ((int)(v - target) >= 0) break;
    }
}
#define PK 2
#define NR 4
__device__ __forceinline__ void hint_wait2(const unsigned int* p, uint32_t target, uint32_t slot) {
    asm volatile("st.shared.b32 [%0], %1;" ::"r"(slot), "r"(target - 0x40000000u) : "memory");
#pragma unroll 1
    for (int it = 0; it < SPIN_LIMIT; it++) {
        asm volatile("cp.async.cg.shared.global [%0], [%1], 16;" ::"r"(slot), "l"(p) : "memory");
        uint32_t v = 0;
#pragma unroll
        for (int k = 0; k < PK; k++) {
            asm volatile("ld.volatile.shared.b32 %0, [%1];" : "=r"(v) : "r"(slot + (v & 0)) : "memory");
            asm volatile("" : "+r"(v));
        }
        if ((int)(v - target) >= 0) break;
    }
}
__device__ __forceinline__ void bulk_load(uint32_t dst, const void* src, uint32_t bytes, uint32_t bar) {
    asm volatile("cp.async.bulk.shared::cluster.global.mbarrier::complete_tx::bytes [%0], [%1], %2, [%3];"
                 ::"r"(dst), "l"(src), "r"(bytes), "r"(bar) : "memory");
}
__device__ __forceinline__ void reld32(uint32_t& v, const void* p, uint32_t cond) {
    asm volatile("{\n.reg .pred p;\nsetp.ne.u32 p, %2, 0;\n@p ld.relaxed.gpu.global.b32 %0, [%1];\n}\n"
                 : "+r"(v) : "l"(p), "r"(cond) : "memory");
}
__device__ __forceinline__ void reld128(uint32_t* a, const void* p, uint32_t cond) {
    asm volatile("{\n.reg .pred p;\n.reg .b128 t;\nsetp.ne.u32 p, %5, 0;\nmov.b128 t, {%0,%1,%2,%3};\n"
                 "@p ld.relaxed.gpu.global.b128 t, [%4];\nmov.b128 {%0,%1,%2,%3}, t;\n}\n"
                 : "+r"(a[0]), "+r"(a[1]), "+r"(a[2]), "+r"(a[3]) : "l"(p), "r"(cond) : "memory");
}
__device__ __forceinline__ void sts16(uint32_t dst, uint32_t a, uint32_t b, uint32_t c, uint32_t d) {
    asm volatile("st.shared.v4.b32 [%0], {%1,%2,%3,%4};" ::"r"(dst), "r"(a), "r"(b), "r"(c), "r"(d) : "memory");
}
__device__ __forceinline__ void tma_load2(uint32_t dst, const CUtensorMap* tm, int c0, uint32_t bar) {
    asm volatile(
        "cp.async.bulk.tensor.2d.shared::cluster.global.mbarrier::complete_tx::bytes [%0], [%1, {%2, %3}], [%4];"
        ::"r"(dst), "l"(tm), "r"(c0), "r"(0), "r"(bar) : "memory");
}
template <int D = 512>
__device__ __forceinline__ void ld_frag(uint32_t* a, const uint4* p) {
    asm volatile("{\n.reg .b128 t, u;\nld.relaxed.gpu.global.b128 t, [%8];\nld.relaxed.gpu.global.b128 u, [%8+%9];\n"
                 "mov.b128 {%0,%1,%2,%3}, t;\nmov.b128 {%4,%5,%6,%7}, u;\n}\n"
                 : "=r"(a[0]), "=r"(a[1]), "=r"(a[2]), "=r"(a[3]), "=r"(a[4]), "=r"(a[5]), "=r"(a[6]), "=r"(a[7])
                 : "l"(p), "n"(D) : "memory");
}
template <int D = 512>
__device__ __forceinline__ void reld_frag(uint32_t* a, const uint4* p, uint32_t cond) {
    asm volatile("{\n.reg .pred p;\n.reg .b128 t, u;\nsetp.ne.u32 p, %9, 0;\n"
                 "mov.b128 t, {%0,%1,%2,%3};\nmov.b128 u, {%4,%5,%6,%7};\n"
                 "@p ld.relaxed.gpu.global.b128 t, [%8];\n@p ld.relaxed.gpu.global.b128 u, [%8+%10];\n"
                 "mov.b128 {%0,%1,%2,%3}, t;\nmov.b128 {%4,%5,%6,%7}, u;\n}\n"
                 : "+r"(a[0]), "+r"(a[1]), "+r"(a[2]), "+r"(a[3]), "+r"(a[4]), "+r"(a[5]), "+r"(a[6]), "+r"(a[7])
                 : "l"(p), "r"(cond), "n"(D) : "memory");
}
__device__ __forceinline__ void settle_frags(uint32_t (*a)[8]) {
    uint32_t z = 0;
#pragma unroll
    for (int i = 0; i < 5; i++) z |= a[i][0] & a[i][4];
    asm volatile("" ::"r"(z));
}
__device__ __forceinline__ void wgmma_n192_rs(float* d, const uint32_t* a, uint32_t db, int scale_d) {
    asm volatile("{\n.reg .pred p;\n.reg .b64 ds;\nmov.b64 ds, {%100, 0x40000040};\nsetp.ne.b32 p, %101, 0;\n"
        "wgmma.mma_async.sync.aligned.m64n192k16.f32.bf16.bf16 "
        "{%0, %1, %2, %3, %4, %5, %6, %7, %8, %9, %10, %11, %12, %13, %14, %15, "
        "%16, %17, %18, %19, %20, %21, %22, %23, %24, %25, %26, %27, %28, %29, %30, %31, "
        "%32, %33, %34, %35, %36, %37, %38, %39, %40, %41, %42, %43, %44, %45, %46, %47, "
        "%48, %49, %50, %51, %52, %53, %54, %55, %56, %57, %58, %59, %60, %61, %62, %63, "
        "%64, %65, %66, %67, %68, %69, %70, %71, %72, %73, %74, %75, %76, %77, %78, %79, "
        "%80, %81, %82, %83, %84, %85, %86, %87, %88, %89, %90, %91, %92, %93, %94, %95}, "
        "{%96, %97, %98, %99}, ds, p, 1, 1, 1;\n}\n"
        : "+f"(d[0]), "+f"(d[1]), "+f"(d[2]), "+f"(d[3]), "+f"(d[4]), "+f"(d[5]), "+f"(d[6]), "+f"(d[7]),
          "+f"(d[8]), "+f"(d[9]), "+f"(d[10]), "+f"(d[11]), "+f"(d[12]), "+f"(d[13]), "+f"(d[14]), "+f"(d[15]),
          "+f"(d[16]), "+f"(d[17]), "+f"(d[18]), "+f"(d[19]), "+f"(d[20]), "+f"(d[21]), "+f"(d[22]), "+f"(d[23]),
          "+f"(d[24]), "+f"(d[25]), "+f"(d[26]), "+f"(d[27]), "+f"(d[28]), "+f"(d[29]), "+f"(d[30]), "+f"(d[31]),
          "+f"(d[32]), "+f"(d[33]), "+f"(d[34]), "+f"(d[35]), "+f"(d[36]), "+f"(d[37]), "+f"(d[38]), "+f"(d[39]),
          "+f"(d[40]), "+f"(d[41]), "+f"(d[42]), "+f"(d[43]), "+f"(d[44]), "+f"(d[45]), "+f"(d[46]), "+f"(d[47]),
          "+f"(d[48]), "+f"(d[49]), "+f"(d[50]), "+f"(d[51]), "+f"(d[52]), "+f"(d[53]), "+f"(d[54]), "+f"(d[55]),
          "+f"(d[56]), "+f"(d[57]), "+f"(d[58]), "+f"(d[59]), "+f"(d[60]), "+f"(d[61]), "+f"(d[62]), "+f"(d[63]),
          "+f"(d[64]), "+f"(d[65]), "+f"(d[66]), "+f"(d[67]), "+f"(d[68]), "+f"(d[69]), "+f"(d[70]), "+f"(d[71]),
          "+f"(d[72]), "+f"(d[73]), "+f"(d[74]), "+f"(d[75]), "+f"(d[76]), "+f"(d[77]), "+f"(d[78]), "+f"(d[79]),
          "+f"(d[80]), "+f"(d[81]), "+f"(d[82]), "+f"(d[83]), "+f"(d[84]), "+f"(d[85]), "+f"(d[86]), "+f"(d[87]),
          "+f"(d[88]), "+f"(d[89]), "+f"(d[90]), "+f"(d[91]), "+f"(d[92]), "+f"(d[93]), "+f"(d[94]), "+f"(d[95])
        : "r"(a[0]), "r"(a[1]), "r"(a[2]), "r"(a[3]), "r"(db), "r"(scale_d));
}
__device__ __forceinline__ void wgmma_n128_rs(float* d, const uint32_t* a, uint32_t db, int scale_d) {
    asm volatile("{\n.reg .pred p;\n.reg .b64 ds;\nmov.b64 ds, {%68, 0x40000040};\nsetp.ne.b32 p, %69, 0;\n"
        "wgmma.mma_async.sync.aligned.m64n128k16.f32.bf16.bf16 "
        "{%0, %1, %2, %3, %4, %5, %6, %7, %8, %9, %10, %11, %12, %13, %14, %15, "
        "%16, %17, %18, %19, %20, %21, %22, %23, %24, %25, %26, %27, %28, %29, %30, %31, "
        "%32, %33, %34, %35, %36, %37, %38, %39, %40, %41, %42, %43, %44, %45, %46, %47, "
        "%48, %49, %50, %51, %52, %53, %54, %55, %56, %57, %58, %59, %60, %61, %62, %63}, "
        "{%64, %65, %66, %67}, ds, p, 1, 1, 1;\n}\n"
        : "+f"(d[0]), "+f"(d[1]), "+f"(d[2]), "+f"(d[3]), "+f"(d[4]), "+f"(d[5]), "+f"(d[6]), "+f"(d[7]),
          "+f"(d[8]), "+f"(d[9]), "+f"(d[10]), "+f"(d[11]), "+f"(d[12]), "+f"(d[13]), "+f"(d[14]), "+f"(d[15]),
          "+f"(d[16]), "+f"(d[17]), "+f"(d[18]), "+f"(d[19]), "+f"(d[20]), "+f"(d[21]), "+f"(d[22]), "+f"(d[23]),
          "+f"(d[24]), "+f"(d[25]), "+f"(d[26]), "+f"(d[27]), "+f"(d[28]), "+f"(d[29]), "+f"(d[30]), "+f"(d[31]),
          "+f"(d[32]), "+f"(d[33]), "+f"(d[34]), "+f"(d[35]), "+f"(d[36]), "+f"(d[37]), "+f"(d[38]), "+f"(d[39]),
          "+f"(d[40]), "+f"(d[41]), "+f"(d[42]), "+f"(d[43]), "+f"(d[44]), "+f"(d[45]), "+f"(d[46]), "+f"(d[47]),
          "+f"(d[48]), "+f"(d[49]), "+f"(d[50]), "+f"(d[51]), "+f"(d[52]), "+f"(d[53]), "+f"(d[54]), "+f"(d[55]),
          "+f"(d[56]), "+f"(d[57]), "+f"(d[58]), "+f"(d[59]), "+f"(d[60]), "+f"(d[61]), "+f"(d[62]), "+f"(d[63])
        : "r"(a[0]), "r"(a[1]), "r"(a[2]), "r"(a[3]), "r"(db), "r"(scale_d));
}
__device__ __forceinline__ void wgmma_n64_rs(float* d, const uint32_t* a, uint32_t db, int scale_d) {
    asm volatile("{\n.reg .pred p;\n.reg .b64 ds;\nmov.b64 ds, {%36, 0x40000040};\nsetp.ne.b32 p, %37, 0;\n"
        "wgmma.mma_async.sync.aligned.m64n64k16.f32.bf16.bf16 "
        "{%0, %1, %2, %3, %4, %5, %6, %7, %8, %9, %10, %11, %12, %13, %14, %15, "
        "%16, %17, %18, %19, %20, %21, %22, %23, %24, %25, %26, %27, %28, %29, %30, %31}, "
        "{%32, %33, %34, %35}, ds, p, 1, 1, 1;\n}\n"
        : "+f"(d[0]), "+f"(d[1]), "+f"(d[2]), "+f"(d[3]), "+f"(d[4]), "+f"(d[5]), "+f"(d[6]), "+f"(d[7]),
          "+f"(d[8]), "+f"(d[9]), "+f"(d[10]), "+f"(d[11]), "+f"(d[12]), "+f"(d[13]), "+f"(d[14]), "+f"(d[15]),
          "+f"(d[16]), "+f"(d[17]), "+f"(d[18]), "+f"(d[19]), "+f"(d[20]), "+f"(d[21]), "+f"(d[22]), "+f"(d[23]),
          "+f"(d[24]), "+f"(d[25]), "+f"(d[26]), "+f"(d[27]), "+f"(d[28]), "+f"(d[29]), "+f"(d[30]), "+f"(d[31])
        : "r"(a[0]), "r"(a[1]), "r"(a[2]), "r"(a[3]), "r"(db), "r"(scale_d));
}
#define SLOT 12288
#define NSLOT 16
#define PS1 680
#define PT 2592
#define SM_W (2 * SLOT)
#define WB(b) (((b) & 1) ? -4096 - 2048 * ((b) & 2) : 32768 - 2048 * (b))
#define SM_MODA (5 * SLOT)
#define SM_MODB (SM_MODA + 20480)
#define SM_SC (SM_MODB + 20480)
#define SM_SV (SM_SC + 5120)
#define SM_MP (SM_SV + 1280)
#define SM_FT (11 * SLOT)
#define SM_S1 (NSLOT * SLOT - 8 * PS1 * 8)
#define SM_T SM_S1
#define SM_Q (SM_T + 8 * PT)
#define SM_XT (NSLOT * SLOT)
#define XP 1296
#define SM_TW (SM_XT + 16 * XP)
#define SM_POS SM_TW
#define SM_TS (SM_TW + 2560)
#define SM_RED (SM_TW + 3584)
#define SM_B2 (SM_TW + 4736)
#define SM_BB (SM_TW + 5248)
#define SM_ONE (SM_TW + 7808)
#define SM_WMX (SM_TW + 7824)
#define SM_S16 (12 * SLOT)
#define B_S (SM_TW + 8368)
#define B_T (SM_TW + 8376)
#define B_M (SM_TW + 8360)
#define SM_GA (SM_TW + 9856)
#define SM_SB (SM_GA + 1280)
#define SM_CB (SM_SB + 1280)
#define SM_GB (SM_CB + 1280)
#define SM_BAR (SM_GB + 1280)
#define B_FULL(s) (SM_XT + 1280 + XP * (s))
#define B_EMPTY(s) (SM_XT + 1288 + XP * (s))
#define B_CH(c) (SM_BAR + 8 * (c))
#define B_W (SM_BAR + 40)
#define B_Q B_CH(3)
#define B_X(w) (SM_BAR + 48 + 8 * (w))
#define SM_SCL (SM_BAR + 112)
#define SMEM_TOTAL (SM_BAR + 128)
#define FWX 3
#define HS1 32
#define HS2 48
#define NB 5
#define HD 800
#define AD0 850
#define AD1 500
#define WD 4200
#define HV2 8
#define SP0 2
#define HP0 0
#define HP1 0
#define HP2 0
#define SP1 2
#define XDC 1700
#define STAG 5

__device__ __forceinline__ void w1_issue(int it0, int it1, uint32_t sbase, int j, const CUtensorMap* tw1) {
#pragma unroll 1
    for (int it = it0; it < it1; it++) {
        const uint32_t bar = sbase + B_FULL(it);
        mbar_expect_tx(bar, SLOT);
        tma_load3(sbase + it * SLOT, tw1, 32 * it, 3 * j, bar);
    }
}
__device__ __forceinline__ void mod_issue(const bf16* wmod, int u, int row0, int n, uint32_t st, int lane) {
    const bf16* src = wmod + (size_t)(row0 + (lane >> 1)) * 3840 + 16 * u + 8 * (lane & 1);
    uint32_t dst = st + (row0 + (lane >> 1)) * 32 + (((lane ^ (lane >> 3)) & 1) << 4);
#pragma unroll 1
    for (int i = 0; i < n; i += 5) {
#pragma unroll
        for (int k = 0; k < 5; k++) cp_async16(dst + 512 * k, src + (size_t)k * 16 * 3840);
        dst += 2560;
        src += 5 * 16 * 3840;
    }
}
#define ONES2 0x3f803f80u
__device__ __forceinline__ void ln_mma(const uint32_t* xa, uint32_t K0, uint32_t K1, float* sd, float* g1, float* g2) {
    uint32_t a[4] = {hsub2(xa[0], K0), hsub2(xa[1], K1), hsub2(xa[2], K0), hsub2(xa[3], K1)};
    mma_acc(sd, a, ONES2, ONES2);
    mma_acc(g1, a, a[0], a[2]);
    mma_acc(g2, a, a[1], a[3]);
}

template <int NU>
__device__ __forceinline__ void send_chunk(const float* acc, uint4* dst, uint32_t tag16, uint32_t loc, uint32_t sdst,
                                           uint32_t sbar) {
#pragma unroll
    for (int u = 0; u < NU; u++) {
        float e = __uint_as_float(((__float_as_uint(acc[8 * u]) + 0x10000u) & 0xfffe0000u) | tag16);
        asm volatile("{\n.reg .pred p;\n.reg .b128 t;\nsetp.ne.u32 p, %5, 0;\nmov.b128 t, {%1,%2,%3,%4};\n"
                     "@p st.async.weak.shared::cluster.mbarrier::complete_tx::bytes.v4.b32 [%6], {%1,%2,%3,%4}, [%7];\n"
                     "@!p st.relaxed.gpu.global.b128 [%0], t;\n}\n"
                     ::"l"(dst + u * 32), "r"(pack_bf2(e, acc[8 * u + 1])), "r"(pack_bf2(acc[8 * u + 2], acc[8 * u + 3])),
                       "r"(pack_bf2(acc[8 * u + 4], acc[8 * u + 5])), "r"(pack_bf2(acc[8 * u + 6], acc[8 * u + 7])),
                       "r"(loc), "r"(sdst + u * 1024), "r"(sbar) : "memory");
    }
}
struct Map3 { CUtensorMap m[12]; };
#define tfa_r tw.m[3]
#define tfa_i tw.m[4]
#define tfb_r tw.m[5]
#define tfb_i tw.m[6]
#define tfc_r tw.m[7]
#define tfc_i tw.m[8]
#define tq tw.m[9]
#define tq16 tw.m[10]
#define LP(c) ((c) == 0 ? SM_TW + 5504 : ((c) == 1 ? 0 : SM_TW))

__global__ void __cluster_dims__(2, 1, 1) __launch_bounds__(384, 1)
fused_kernel(const bf16* __restrict__ x, const bf16* __restrict__ c, const bf16* __restrict__ wmod, Scratch* scr,
             const uint32_t* __restrict__ gt, bf16* __restrict__ out, const bf16* __restrict__ w1,
             const __grid_constant__ Map3 tw) {
    extern __shared__ __align__(1024) unsigned char smem[];
    const uint32_t sbase = smem_u32(smem);
    const int t = threadIdx.x, g = blockIdx.x, lane = t & 31, warp = __shfl_sync(0xffffffffu, t >> 5, 0);
    const int q = lane & 3, r = lane >> 2, j = g & 7;
#define XISSUE                                                                                    \
    {                                                                                             \
        mbar_expect_tx(sbase + B_X(warp), 2560);                                                  \
        const bf16* src = x + (size_t)(g + 256 * warp) * 640;                                     \
        bulk_load(sbase + SM_XT + 2 * warp * XP, src, 1280, sbase + B_X(warp));                   \
        bulk_load(sbase + SM_XT + (2 * warp + 1) * XP, src + 128 * 640, 1280, sbase + B_X(warp)); \
        TS(27, t == 0);                                                                           \
    }
    const bool mir = g >= 16 && j == 0;
    TS(0, t == 32);
    TW(0);
    uint32_t cl0;
    asm volatile("mov.u32 %0, %%clock;" : "=r"(cl0));
    if (warp >= 8 && lane == 0) {
        l2_prefetch(wmod + (size_t)(5 * g + warp - 8) * 3840, 2560);
        if (warp == 8) l2_prefetch(wmod + (size_t)(5 * g + 4) * 3840, 2560);
    }
    uint32_t cv[3];
    if (warp >= 8) {
        __syncwarp();
        if (g < 80) mod_issue(wmod, g, 160 * (warp - 8), 10, sbase + SM_MODA, lane);
#pragma unroll
        for (int i = 0; i < 3; i++)
            cv[i] = (i < 2 || lane < 16) ? ldg_nc32(c + 2 * (80 * (warp - 8) + lane + 32 * i)) : 0u;
    }
    TS(28, t == 256);
    if (warp < 8 && lane == 0) {
        mbar_init(sbase + B_X(warp), 1);
        mbar_init(sbase + B_FULL(2 * warp), 1);
        mbar_init(sbase + B_EMPTY(2 * warp), 8);
        mbar_init(sbase + B_FULL(2 * warp + 1), 1);
        mbar_init(sbase + B_EMPTY(2 * warp + 1), 8);
        if (warp < 6) mbar_init(sbase + B_CH(warp), warp < 3 ? 8 : (warp == 4 ? (g == 127 ? 11 : 10) : 1));
        if (warp == 6) {
            mbar_init(sbase + B_S, 1);
            mbar_init(sbase + B_T, 1);
            mbar_init(sbase + B_M, 1);
        }
        if (warp >= 6) sts16(sbase + SM_ONE + 16 * (7 - warp), warp - 6, 0, 0, 0);
        asm volatile("fence.mbarrier_init.release.cluster;" ::: "memory");
        asm volatile("fence.proxy.async.shared::cta;" ::: "memory");
        if (warp == 5) {
#pragma unroll
            for (int i = 0; i < 12; i++)
                asm volatile("prefetch.tensormap [%0];" ::"l"(&tw.m[i]) : "memory");
        }
        if (warp == 6) {
            mbar_expect_tx(sbase + B_T, 15872);
            bulk_load(sbase + SM_POS, gt + 640 * (g & 1), 2560, sbase + B_T);
            bulk_load(sbase + SM_B2, gt + 1280, 3072, sbase + B_T);
            bulk_load(sbase + SM_FT, gt + 2048, 10240, sbase + B_T);
        }
    }
    __syncwarp();
    asm volatile("barrier.cluster.arrive.relaxed.aligned;" ::: "memory");
    uint32_t epv, ep;
    asm volatile("ld.relaxed.gpu.global.u32 %0, [%1];" : "=r"(epv) : "l"(g_epoch + lane) : "memory");
    if (warp >= 8) {
        const int e = t & 127, num = (((e >> 4) * (128 * (e & 15) + g) + 1024) & 2047) - 1024;
        const float an = (float)num * (6.283185307179586f / 2048.0f);
        float2 v = make_float2(__cosf(an), -__sinf(an));
        if (e < 16) v = make_float2(0.5f, (t & 1) ? -0.5f : 0.5f);
        *reinterpret_cast<float2*>(smem + SM_TS + 8 * e) = v;
    }
    TS(29, t == 0);
    TW(1);
    TS(30, t == 256);

    const int bb0 = 20 * (warp & 1) + (warp >> 1);
    uint32_t Pb[4][2];
    if (warp < 10) {
        asm volatile("ld.global.nc.b32 %0, [%8];\nld.global.nc.b32 %1, [%8+4];\nld.global.nc.b32 %2, [%8+8];\nld.global.nc.b32 %3, [%8+12];\n"
                     "ld.global.nc.b32 %4, [%8+512];\nld.global.nc.b32 %5, [%8+516];\nld.global.nc.b32 %6, [%8+520];\nld.global.nc.b32 %7, [%8+524];"
                     : "=r"(Pb[0][0]), "=r"(Pb[0][1]), "=r"(Pb[1][0]), "=r"(Pb[1][1]), "=r"(Pb[2][0]), "=r"(Pb[2][1]), "=r"(Pb[3][0]), "=r"(Pb[3][1])
                     : "l"(gt + 4608 + 256 * warp + 4 * lane));
    }
    auto filter_issue = [&]() {
        const int f = g >> 4, kc = g & 15;
        const uint32_t bar = sbase + B_W;
        mbar_expect_tx(bar, (g < 16 ? 24576 : 28672) + (mir ? 4096 : 0) + (g == 127 ? 16384 : 0));
        if (g < 16) {
    #pragma unroll 1
            for (int b = 0; b < 2; b++) {
                tma_load2(sbase + SM_W + 6144 * b, &tfc_r, (20 * g + 2568 * b) & ~7, bar);
                tma_load2(sbase + SM_W + 12288 + 6144 * b, &tfc_i, (20 * g + 2568 * b) & ~7, bar);
            }
        } else {
            const int c0 = kc >= 8 ? (16 - f) * 321 + 601 - 40 * kc : f * 321 + 40 * kc;
            tma_load2(sbase + SM_W, &tfa_r, c0 & ~7, bar);
            tma_load2(sbase + SM_W + 14336, &tfa_i, c0 & ~7, bar);
        }
    #pragma unroll 1
        for (int b = 0; b < 4; b++) {
            int cb = (b & 1) * 2568 + (b >> 1) * 320;
            if (mir) cb = kc ? f * 321 + 320 : (16 - f) * 321;
            if (g == 127 || (b == 2 && mir)) {
                tma_load2(sbase + SM_W + WB(b), &tfb_r, cb & ~7, bar);
                tma_load2(sbase + SM_W + WB(b) + 2048, &tfb_i, cb & ~7, bar);
            }
        }
    };
    if (warp >= 8) {
#pragma unroll
        for (int i = 0; i < 3; i++)
            if (i < 2 || lane < 16) {
                const int P = 80 * (warp - 8) + lane + 32 * i;
                reinterpret_cast<uint32_t*>(smem + SM_SV)[(P & ~7) + ((P & 3) << 1) + ((P >> 2) & 1)] =
                    pack_bf2(silu1(bf_lo(cv[i])), silu1(bf_hi(cv[i])));
            }
        if (warp >= 10) BAR_ARRIVE(1, 384);
        ep = __shfl_sync(0xffffffffu, epv, 0) + 1;
        TS(31, t == 256);
        float2* mp = reinterpret_cast<float2*>(smem + SM_MP);
#pragma unroll 1
        for (int pass = 0; pass < 3; pass++) {
            int u, row0 = 0, nk = 40;
            uint32_t st = sbase + SM_MODA;
            if (pass == 0) {
                u = g < 80 ? g : -1;
                row0 = 160 * (warp - 8);
                nk = 10;
            } else {
                u = pass == 1 ? (g < 127 ? 80 + g : -1) : (g >= 94 && g < 127 ? 113 + g : -1);
                if (pass == 2) st = sbase + SM_MODB;
                if (pass == 1 && g < 127 && lane == 0) {
                    asm volatile("fence.proxy.async.shared::cta;" ::: "memory");
                    mbar_expect_tx(sbase + B_M, g >= 94 ? 40960 : 20480);
#pragma unroll 1
                    for (int k = 0; k < (g >= 94 ? 8 : 4); k++)
                        asm volatile("cp.async.bulk.tensor.2d.shared::cluster.global.mbarrier::complete_tx::bytes [%0], [%1, {%2, %3}], [%4];"
                                     ::"r"(st + 5120 * k), "l"(&tw.m[11]), "r"(16 * (80 + g + 33 * (k >> 2))), "r"(160 * (k & 3)), "r"(sbase + B_M) : "memory");
                }
                __syncwarp();
                if (g < 127) mbar_wait(sbase + B_M, 0);
            }
            int dw = u * 8 + (lane & 7);
            const uint32_t one = (u >= 40 && u < 80) || (u >= 160 && u < 200) ? ONES2 : 0x80008000u;
            if (u >= 80 && u < 200) {
                const int v = (u - 80) / 40, u1 = u - 80 - 40 * v, w = u1 / 5, m = 2 * (u1 - 5 * w) + ((lane >> 2) & 1);
                const int n = v ? 10 * v + m - 2 : m;
                dw = 640 + 120 * w + (v == 0 && m >= 8 ? 104 + 2 * q + m : 16 * (n >> 2) + 4 * q + (n & 3));
            }
            asm volatile("" : "+r"(dw));
            cp_async_wait_all();
            __syncwarp();
            TS(32, t == 256);
            TW(45 + (pass > 0));
            float2 res = make_float2(0.f, 0.f);
            if (u >= 0) {
                float d0[4] = {0.f, 0.f, 0.f, 0.f}, d1[4] = {0.f, 0.f, 0.f, 0.f};
                uint32_t pa = st + (row0 + (lane & 7) + ((lane >> 1) & 8)) * 32 + ((((lane >> 3) ^ (lane >> 2)) & 1) << 4);
                const uint2* ps = reinterpret_cast<const uint2*>(smem + SM_SV + row0 * 2) + q;
#pragma unroll 1
                for (int k = 0; k < nk; k += 10) {
                    uint32_t a[10][4];
                    uint2 sv[10];
#pragma unroll
                    for (int i = 0; i < 10; i++) {
                        ldsm4t(a[i], pa + 512 * i);
                        sv[i] = ps[4 * i];
                    }
#pragma unroll
                    for (int i = 0; i < 10; i++) mma_acc((i & 1) ? d1 : d0, a[i], sv[i].x, sv[i].y);
                    pa += 5120;
                    ps += 40;
                }
                if (q == 0) {
                    float* mf = reinterpret_cast<float*>(mp) + (warp - 8) * 16 + r;
                    mf[0] = d0[0] + d1[0];
                    mf[8] = d0[2] + d1[2];
                }
            }
            if (pass == 0) {
                BAR_SYNC(8, 128);
                if (warp == 8) {
#pragma unroll
                    for (int w = 0; w < 4; w++) res = cadd(res, mp[8 * w + (lane & 7)]);
                } else u = -1;
            } else {
                __syncwarp();
                res = mp[(warp - 8) * 8 + (lane & 7)];
            }
            if (u >= 0) st_rlx64(&g_mod[(lane >> 3) * 1920 + dw], hadd2(pack_bf2(res.x, res.y), one), ep);
            TS(63, t == 320 && u >= 0);
            if (pass == 0) {
                TS(1, warp == 8 && lane == 0);
                TW(47);
                BAR_SYNC(0, 384);
                if (t == 288) filter_issue();
                __syncwarp();
                if (warp < 10) break;
                const uint4* src = reinterpret_cast<const uint4*>(g_mod + (g & 3) * 1920) + (t - 320);
                uint2 ps[5];
                mbar_wait(sbase + B_T, 0);
#pragma unroll
                for (int i = 0; i < 5; i++) {
                    const bool ca = i > 2 || (i == 2 && warp == 11);
                    ps[i] = reinterpret_cast<const uint2*>(smem + SM_POS + 1280)[t - 320 + 64 * i - (ca ? 160 : 0)];
                    asm volatile("" : "+r"(ps[i].x), "+r"(ps[i].y));
                }
                uint4 w[5];
#pragma unroll 1
                for (int it = 0; it < SPIN_LIMIT; it++) {
                    uint32_t bad = 0;
#pragma unroll
                    for (int i = 0; i < 5; i++) w[i] = ld_rlx128(src + 64 * i);
#pragma unroll
                    for (int i = 0; i < 5; i++) bad |= (w[i].y ^ ep) | (w[i].w ^ ep);
                    if (!bad) break;
                }
                uint32_t mx = 0;
#pragma unroll
                for (int i = 0; i < 5; i++) {
                    const bool ca = i > 2 || (i == 2 && warp == 11);
                    mx = __vmaxu2(mx, __vmaxu2(w[i].x & 0x7fff7fffu, w[i].z & 0x7fff7fffu) + (ca ? 0x02000200u : 0u));
                }
                mx = warp_max16(mx);
                volatile uint32_t* xch = reinterpret_cast<volatile uint32_t*>(smem + SM_SCL);
                if (lane == 0) xch[warp - 10] = mx;
                BAR_SYNC(12, 64);
                const int e1 = min((int)(max(xch[0], xch[1]) >> 7), 252);
#pragma unroll
                for (int i = 0; i < 5; i++) {
                    const bool ca = i > 2 || (i == 2 && warp == 11);
                    const float m = pow2i((ca ? 126 : 129) - e1), m2 = ca ? m : 0.f;
                    const float v[4] = {bf_lo(w[i].x), bf_hi(w[i].x), bf_lo(w[i].z), bf_hi(w[i].z)};
                    unsigned char* sc = smem + SM_SC + (ca ? 2560 : 0);
                    *reinterpret_cast<uint32_t*>(sc + (ps[i].x & 0xffffu)) = pack_h2(m * v[0], m2 * v[0]);
                    *reinterpret_cast<uint32_t*>(sc + (ps[i].x >> 16)) = pack_h2(m * v[1], m2 * v[1]);
                    *reinterpret_cast<uint32_t*>(sc + (ps[i].y & 0xffffu)) = pack_h2(m * v[2], m2 * v[2]);
                    *reinterpret_cast<uint32_t*>(sc + (ps[i].y >> 16)) = pack_h2(m * v[3], m2 * v[3]);
                }
                BAR_ARRIVE(3, 384);
                BAR_ARRIVE(2, 384);
                TS(7, t == 320);
                TW(42);
                if (warp == 11) break;
            }
        }
    } else {
        BAR_ARRIVE(0, 384);
        BAR_SYNC(9, 256);
        if (lane == 0) {
#pragma unroll 1
            for (int i = 0; i < 1000; i++) {
                uint32_t c1;
                asm volatile("mov.u32 %0, %%clock;" : "=r"(c1));
                if (c1 - cl0 >= XDC) break;
            }
            XISSUE;
        }
        __syncwarp();
        asm volatile("barrier.cluster.wait.acquire.aligned;" ::: "memory");
        TS(38, t == 0);
        TW(2);
        ep = __shfl_sync(0xffffffffu, epv, 0) + 1;
    }
    const uint32_t hint1 = ep * 128u - HS1, hint2 = ep * 129u - HS2;
    const uint32_t tag = ep & 1;

    const int row = 4 * (g & 7) + ((g >> 3) & 3) + (g & 96);
    const int fw = warp ^ FWX;
#pragma unroll 1
    for (int st = 0; st < 2; st++) {
        asm volatile("" : "+r"(st));
        if (warp < 10) {
            uint32_t A[4][2][4], V[4][4], Bb[5][4], ad[20];
            {
                const uint32_t s2 = (r & 1) ? 0x80008000u : 0u;
#pragma unroll
                for (int i = 0; i < 4; i++)
#pragma unroll
                    for (int e = 0; e < 2; e++) {
                        const uint32_t P = Pb[i][e], R = __byte_perm(P, 0, 0x1032) ^ 0x8000u;
                        A[i][e][0] = P;
                        A[i][e][1] = R;
                        A[i][e][2] = (e ? R : P) ^ s2;
                        A[i][e][3] = e ? P ^ s2 ^ 0x80008000u : R ^ s2;
                        asm volatile("" : "+r"(A[i][e][0]), "+r"(A[i][e][1]), "+r"(A[i][e][2]), "+r"(A[i][e][3]));
                    }
            }
            mbar_wait(sbase + B_T, 0);
#pragma unroll
            for (int b = 0; b < 5; b++) lds16(Bb[b], sbase + SM_BB + 512 * b + 16 * lane);
            const uint32_t gs = 16 * ((warp ^ g) & 1) + 32 * (warp >> 1);
            if (st == 0) {
                const unsigned short* pp = reinterpret_cast<const unsigned short*>(smem + SM_POS) + (fw ? 640 : 0) + 2 * r + 16 * q;
                const uint32_t stg = sbase + SM_Q + fw * 2560, sw = 16 * (fw & 1);
#pragma unroll
                for (int u = 0; u < 20; u += 2) {
                    const uint32_t z = *reinterpret_cast<const uint32_t*>(pp + 32 * (u & 2) + 128 * (u >> 2));
                    ad[u] = stg + ((z & 0xffffu) ^ sw);
                    ad[u + 1] = stg + ((z >> 16) ^ sw);
                    asm volatile("" : "+r"(ad[u]), "+r"(ad[u + 1]));
                }
                float2* red = reinterpret_cast<float2*>(smem + SM_GA);
                uint32_t xq[4];
#pragma unroll
                for (int i = 0; i < 4; i++) {
                    xq[i] = sbase + SM_Q + 128 * gs + 512 * i + ((16 * lane) ^ (32 * ((bb0 + 5 * i) & 2)));
                    asm volatile("" : "+r"(xq[i]));
                }
                const float4* ts = reinterpret_cast<const float4*>(smem + SM_TS) + r * 8 + q;
                if (warp < 8) {
                    const uint32_t xt = sbase + SM_XT + (8 * (warp & 1) + (lane & 7)) * XP + 80 * ((warp & 2) + (lane >> 4) + 4 * ((lane >> 3) & 1) + 2 * (warp & 4));
                    const uint32_t xd = sbase + SM_Q + 64 * (warp & 4) + 128 * (warp & 1) + 4 * (warp & 2) + 16 * (r ^ (4 * (q & 1)));
                    uint32_t pa[10];
#pragma unroll
                    for (int m = 0; m < 5; m++) {
                        const uint32_t z = reinterpret_cast<const uint32_t*>(smem + SM_POS + 1280)[4 * m + q];
                        pa[2 * m] = xd + 128 * (z & 0xffffu);
                        pa[2 * m + 1] = xd + 128 * (z >> 16);
                        asm volatile("" : "+r"(pa[2 * m]), "+r"(pa[2 * m + 1]));
                    }
                    TW(6);
                    if (lane < 8) mbar_wait(sbase + B_X(lane), 0);
                    __syncwarp();
                    TS(2, t == 0);
                    TW(3);
                    uint32_t a[5][4];
#pragma unroll
                    for (int m = 0; m < 5; m++) ldsm4(a[m], xt + 16 * m);
                    const uint32_t K = dup_lo(__shfl_sync(0xffffffffu, a[0][0], lane & 28));
                    float sd[4] = {0.f, 0.f, 0.f, 0.f}, g1[4] = {0.f, 0.f, 0.f, 0.f}, g2[4] = {0.f, 0.f, 0.f, 0.f};
#pragma unroll
                    for (int m = 0; m < 5; m++) {
                        ln_mma(a[m], K, K, sd, g1, g2);
#pragma unroll
                        for (int e = 0; e < 2; e++)
                            asm volatile("st.shared.v2.b32 [%0], {%1,%2};"
                                         ::"r"(pa[2 * m + e]), "r"(__byte_perm(a[m][0], a[m][1], e ? 0x7632 : 0x5410)),
                                           "r"(__byte_perm(a[m][2], a[m][3], e ? 0x7632 : 0x5410)) : "memory");
                    }
                    if (q == (r >> 1)) {
                        const float S = sd[0] + sd[2], Q = ((r & 1) ? g1[1] : g1[0]) + ((r & 1) ? g2[3] : g2[2]);
                        red[(warp >> 1) * 16 + 8 * (warp & 1) + r] = make_float2(fmaf(160.f, bf_lo(K), S), fmaf(S * S, -1.0f / 160.0f, Q));
                    }
                    if (lane == 0) mbar_expect_tx(sbase + B_X(warp), 6144);
                    TS(33, t == 0);
                    TW(4);
                }
                BAR_SYNC(1, 384);
                {
                    uint32_t b[4][4];
#pragma unroll
                    for (int i = 0; i < 4; i++) ldsm4t(b[i], xq[i]);
                    const float4 T[2] = {ts[0], ts[4]};
                    float2 a[4];
#pragma unroll
                    for (int i = 0; i < 4; i++) a[i] = red[16 * i + (lane & 15)];
                    const float tot = (a[0].x + a[1].x) + (a[2].x + a[3].x), m160 = tot * 0.25f;
                    float m2 = (a[0].y + a[1].y) + (a[2].y + a[3].y), m3 = 0.f;
#pragma unroll
                    for (int i = 0; i < 4; i++) m3 = fmaf(a[i].x - m160, a[i].x - m160, m3);
                    m2 = fmaf(m3, 1.0f / 160.0f, m2);
                    const float mean = tot * (1.0f / 640.0f);
                    const float var = bf_round(m2 * (1.0f / 640.0f));
                    const float rs = rcpf(bf_round(sqrtf_a(bf_round(var + 1e-5f))));
                    TS(34, t == 0 && rs != 123.f);
                    const uint32_t mb = pack_bf2(mean, __shfl_xor_sync(0xffffffffu, mean, 1));
                    const uint32_t m0 = __shfl_sync(0xffffffffu, mb, 2 * q), m1 = __shfl_sync(0xffffffffu, mb, 2 * q + 8);
                    uint32_t ah[4], al[4];
#pragma unroll
                    for (int hh = 0; hh < 2; hh++) {
                        const float r0 = __shfl_sync(0xffffffffu, rs, 2 * q + 8 * hh), r1 = __shfl_sync(0xffffffffu, rs, 2 * q + 8 * hh + 1);
                        split2(T[hh].x * r0, T[hh].z * r1, ah[2 * hh], al[2 * hh]);
                        split2(T[hh].y * r0, T[hh].w * r1, ah[2 * hh + 1], al[2 * hh + 1]);
                    }
#pragma unroll
                    for (int i = 0; i < 4; i++)
#pragma unroll
                        for (int h = 0; h < 2; h++) {
                            const uint32_t b0 = hsub2(b[i][2 * h], m0), b1 = hsub2(b[i][2 * h + 1], m1);
                            float d[4];
                            mma_zero(d, al, b0, b1);
                            mma_acc(d, ah, b0, b1);
                            V[2 * h][i] = pack_h2(d[0], d[2]);
                            V[2 * h + 1][i] = pack_h2(d[1], d[3]);
                            asm volatile("" : "+r"(V[2 * h][i]), "+r"(V[2 * h + 1][i]));
                        }
                }
#pragma unroll
                for (int jj = 0; jj < 4; jj++)
                    asm volatile("{\n.reg .pred p;\nsetp.eq.u32 p, %5, 0;\n@p st.shared.v4.b32 [%0], {%1,%2,%3,%4};\n}\n"
                                 ::"r"(sbase + SM_T), "r"(V[jj][0]), "r"(V[jj][1]), "r"(V[jj][2]), "r"(V[jj][3]), "r"(ep) : "memory");
                TS(3, t == 0);
                TW(7);
                BAR_SYNC(3, 384);
                TS(4, t == 0);
                const uint32_t sc = sbase + SM_SC + 160 * q + gs;
                uint32_t S[4][4], C[4][4];
#pragma unroll
                for (int jj = 0; jj < 4; jj++) {
                    lds16(S[jj], sc + 2560 + 640 * jj);
                    C[jj][0] = C[jj][1] = C[jj][2] = C[jj][3] = 0;
                    asm volatile("{\n.reg .pred p;\nsetp.eq.u32 p, %5, 0;\n@p ld.shared.v4.b32 {%0,%1,%2,%3}, [%4];\n}\n"
                                 : "+r"(C[jj][0]), "+r"(C[jj][1]), "+r"(C[jj][2]), "+r"(C[jj][3]) : "r"(sc + 640 * jj), "r"(r) : "memory");
                }
                BAR_ARRIVE(6, 384);
#pragma unroll
                for (int jj = 0; jj < 4; jj++)
#pragma unroll
                    for (int i = 0; i < 4; i++) V[jj][i] = ffma2(V[jj][i], S[jj][i], C[jj][i]);
                TW(8);
            } else {
                const uint32_t stg = sbase + SM_T + fw * PT;
#pragma unroll
                for (int u = 0; u < 20; u++) {
                    ad[u] = stg + 2560 - 4 * (2 * r + 16 * q) - 4 * ((u & 1) + 64 * ((u >> 1) & 1) + 128 * (u >> 2));
                    if (u == 0 && lane == 0) ad[0] = stg;
                    asm volatile("" : "+r"(ad[u]));
                }
                uint32_t pos[2][4], S[4][4];
                const unsigned short* pp = reinterpret_cast<const unsigned short*>(smem + SM_POS) + 40 * q + bb0;
                const uint32_t p1 = (16 * r + q) * 160 + (gs ^ (16 * (r & 1)));
                if (t == 288) {
                    asm volatile("cp.async.bulk.wait_group.read 0;" ::: "memory");
                    hint_wait2(&g_cnt[(8 + (g & (NR - 1))) * 32], hint2, sbase + SM_TW + 7856);
                    mbar_expect_tx(sbase + B_Q, 129 * 160);
                    tma_load2(sbase + SM_Q, &tq, 40 * row, sbase + B_Q);
                    TS(37, true);
                    TW(27);
                }
                __syncwarp();
                mbar_wait(sbase + B_S, 0);
#pragma unroll
                for (int jj = 0; jj < 4; jj++)
#pragma unroll
                    for (int i = 0; i < 4; i++) {
                        const uint32_t z = pp[160 * jj + 5 * i];
                        if (jj & 1) {
                            pos[jj >> 1][i] = sbase + SM_Q + z;
                            asm volatile("" : "+r"(pos[jj >> 1][i]));
                        }
                        S[jj][i] = dup_lo(reinterpret_cast<const unsigned short*>(smem + SM_S16)[r ? 160 * r + 10 * q + 40 * jj + warp : (z >> 4) ^ (g & 1)]);
                        asm volatile("" : "+r"(S[jj][i]));
                    }
                uint32_t px0 = (t & 0x3e3) == 0 ? sbase + SM_Q + 20480 : pos[0][0] - 1280, px1 = (t & 0x3e3) == 0 ? sbase + SM_Q + 20484 : pos[1][0] + 1280;
                uint32_t pv = sbase + SM_Q + p1;
                asm volatile("" : "+r"(px0), "+r"(px1), "+r"(pv));
                TW(30);
                mbar_wait(sbase + B_Q, 1);
                TW(31);
#pragma unroll 1
                for (int it = 0; it < SPIN_LIMIT; it++) {
                    uint32_t Vb[4][4];
#pragma unroll
                    for (int jj = 0; jj < 4; jj++) lds16(V[jj], pv + 640 * jj);
#pragma unroll
                    for (int i = 0; i < 4; i++) {
                        Vb[0][i] = lds4(i ? pos[0][i] - 1280 : px0);
                        Vb[1][i] = lds4(pos[0][i]);
                        Vb[2][i] = lds4(i ? pos[1][i] + 1280 : px1);
                        Vb[3][i] = lds4(pos[1][i]);
                    }
#pragma unroll
                    for (int jj = 0; jj < 4; jj++)
#pragma unroll
                        for (int i = 0; i < 4; i++) V[jj][i] = r ? V[jj][i] : Vb[jj][i];
                    uint32_t bad = or3(or3(V[0][0], V[0][1], V[0][2]), or3(V[0][3], V[1][0], V[1][1]), or3(V[1][2], V[1][3], V[2][0]));
                    bad = or3(bad, or3(V[2][1], V[2][2], V[2][3]), or3(or3(V[3][0], V[3][1], V[3][2]), V[3][3], 0));
                    if (!__any_sync(0xffffffffu, bad & 1)) break;
                    const char* gp = reinterpret_cast<const char*>(g_I) + row * 160;
#pragma unroll 1
                    for (int e = 0; e < 16; e++) {
                        uint32_t z = r ? p1 + 160 * (e & 12) + 4 * (e & 3) : pp[40 * (e & 12) + 5 * (e & 3)];
                        const uint32_t w = lds4(sbase + SM_Q + z);
                        z &= 0xfff0u;
                        if (w & 1) cp_async16(sbase + SM_Q + z, gp + z + ((z * 6554u) >> 20) * 20320u);
                    }
                    cp_async_wait_all();
                }
#pragma unroll
                for (int jj = 0; jj < 4; jj++)
#pragma unroll
                    for (int i = 0; i < 4; i++) V[jj][i] = fmul2(V[jj][i], S[jj][i]);
                TS(10, t == 0);
                TW(32);
            }
            {
                uint32_t O[4][4];
#pragma unroll
                for (int i = 0; i < 4; i++) {
                    const uint32_t u0 = V[0][i], u1 = V[1][i], u2 = V[2][i], u3 = V[3][i];
                    float de[4], dd[4];
                    mma_h0(de, A[i][0][0], A[i][0][1], A[i][0][2], A[i][0][3], fadd2(u0, u2), fadd2(u1, u3));
                    mma_h0(dd, A[i][1][0], A[i][1][1], A[i][1][2], A[i][1][3], fsub2(u0, u2), fsub2(u1, u3));
                    O[0][i] = pack_h2(de[0], de[2]);
                    O[1][i] = pack_h2(de[1], de[3]);
                    O[2][i] = pack_h2(dd[0], dd[2]);
                    O[3][i] = pack_h2(dd[1], dd[3]);
                }
                const uint32_t dst = sbase + SM_T + 2 * q * PT + (warp >> 1) * 512 + r * 32 + 16 * ((warp ^ (r >> 2) ^ (q >> 1)) & 1);
#pragma unroll
                for (int u = 0; u < 4; u++) sts16(dst + (u & 1) * PT + (u >> 1) * 256, O[u][0], O[u][1], O[u][2], O[u][3]);
            }
            TW(9 + 24 * st);
            if (warp >= 8) {
                BAR_ARRIVE(2, 384);
            } else {
                const uint32_t lm = sbase + SM_T + fw * PT + (lane & 15) * 32 + 16 * (((lane >> 4) ^ (lane >> 2) ^ (fw >> 2)) & 1);
                BAR_SYNC(2, 384);
                TS(5, t == 0 && st == 0);
                TS(11, t == 0 && st == 1);
                uint32_t acc[5][2][2];
#pragma unroll
                for (int b = 0; b < 5; b++) {
                    uint32_t a[4];
                    ldsm4(a, lm + 512 * b);
                    mma_g0(acc[b][0], a[0], a[1], a[2], a[3], Bb[b][0], Bb[b][1]);
                    mma_g0(acc[b][1], a[0], a[1], a[2], a[3], Bb[b][2], Bb[b][3]);
                }
                if (st == 0) BAR_ARRIVE(10, 288);
                const uint32_t tg = st ? 0u : 0x00010001u;
                __syncwarp();
#pragma unroll
                for (int u = 0; u < 4; u++) {
                    uint32_t y[5];
#pragma unroll
                    for (int b = 0; b < 5; b++) y[b] = acc[b][u >> 1][u & 1];
                    dft5(y);
#pragma unroll
                    for (int d = 0; d < 5; d++) {
                        asm volatile("st.shared.b32 [%0], %1;" ::"r"(ad[4 * d + u]), "r"(y[d] | tg) : "memory");
                    }
                }
                TW(12 + 24 * st);
                if (st == 0) {
                    if (fw == 0 && lane >= 17 && lane < 21)
                        asm volatile("st.shared.b32 [%0], %1;"
                                     ::"r"(sbase + SM_Q + (lane < 19 ? 8 * (lane - 17) + 16 * (g & 1) : 20488 + 4 * (lane - 19))), "r"(0x00010001u) : "memory");
                    asm volatile("fence.proxy.async.shared::cta;" ::: "memory");
                    __syncwarp();
                    TW(13);
                    if (lane == 0) {
                        asm volatile("cp.async.bulk.tensor.2d.global.shared::cta.bulk_group [%0, {%1, %2}], [%3];"
                                     ::"l"(&tq16), "r"(40 * row), "r"(16 * fw), "r"(sbase + SM_Q + fw * 2560) : "memory");
                        if (fw == 0)
                            asm volatile("cp.async.bulk.global.shared::cta.bulk_group [%0], [%1], 16;"
                                         ::"l"(g_I + 128 * 5120 + row * 40), "r"(sbase + SM_Q + 20480) : "memory");
                        asm volatile("cp.reduce.async.bulk.global.shared::cta.bulk_group.add.u32 [%0], [%1], 16;"
                                     ::"l"(&g_cnt[fw * 32]), "r"(sbase + SM_ONE) : "memory");
                        asm volatile("cp.async.bulk.commit_group;" ::: "memory");
                    }
                    __syncwarp();
                    TS(6, t == 0);
                    TW(14);
                }
            }
        } else if (st == 0) {
            if (warp == 10) {
                BAR_ARRIVE(6, 384);
            } else {
                mbar_wait(sbase + B_CH(4), 0);
                if (lane == 0) {
                    uint32_t z[4];
                    lds16(z, sbase + SM_WMX);
                    st_rlx128(&g_wm[g], z[0], z[1], z[2] | (z[3] << 24), ep);
                }
                uint4 w[4];
                mbar_wait(sbase + B_Q, 0);
                if (lane == 0) {
                    l2_prefetch(reinterpret_cast<const char*>(w1) + g * 15360, 15360);
                }
#pragma unroll 1
                for (int it = 0; it < SPIN_LIMIT; it++) {
                    uint32_t bad = 0;
#pragma unroll
                    for (int i = 0; i < 4; i++) w[i] = ld_rlx128(g_wm + 32 * i + lane);
#pragma unroll
                    for (int i = 0; i < 4; i++) bad |= w[i].w ^ ep;
                    if (!bad) break;
                }
                const int ew = __reduce_max_sync(0xffffffffu, max(max(w[0].z, w[1].z), max(w[2].z, w[3].z)) >> 24);
                unsigned char* raw = smem + SM_S16 + 2576;
#pragma unroll
                for (int i = 0; i < 4; i++) reinterpret_cast<uint4*>(raw)[32 * i + lane] = w[i];
                if (lane == 31) {
                    const uint2 xm = *reinterpret_cast<const uint2*>(smem + SM_SCL);
                    const int tt = min(min((int)(max(xm.x, xm.y) >> 7), 252) - 126 + ew - 112, 254);
                    *reinterpret_cast<uint32_t*>(raw + 2048) = __byte_perm(w[3].z, 0, 0x22);
                    const int k1 = max((tt - 20) >> 1, -127), k2 = max(tt - 20 - k1, -127);
                    *reinterpret_cast<uint32_t*>(smem + SM_SCL + 8) = (uint32_t)((k1 + 127) << 7) | (uint32_t)((k2 + 127) << 23);
                }
                {
                    const float2* ts = reinterpret_cast<const float2*>(smem + SM_TS) + q * 16 + r;
                    uint32_t fh[4], fl[4];
#pragma unroll
                    for (int i = 0; i < 4; i++) {
                        const float2 T = ts[(i >> 1) * 64 + (i & 1) * 8];
                        fh[i] = pack_h2(1.6f * T.x, 1.6f * T.y);
                        const float2 h = unpack_h2(fh[i]);
                        fl[i] = pack_h2(fmaf(1.6f, T.x, -h.x), fmaf(1.6f, T.y, -h.y));
                    }
                    __syncwarp();
                    sts16(sbase + SM_TS + 16 * lane, fh[0], fh[1], fh[2], fh[3]);
                    sts16(sbase + SM_TS + 512 + 16 * lane, fl[0], fl[1], fl[2], fl[3]);
                }
                __syncwarp();
#pragma unroll 2
                for (int i = 0; i < 21; i++) {
                    const int P = min(lane + 32 * i, 640);
                    const uint32_t z = *reinterpret_cast<const unsigned short*>(raw + 2 * P + 6 * ((P * 205) >> 10));
                    reinterpret_cast<uint32_t*>(smem + SM_S16)[P] =
                        pack_h2(__int_as_float(max((int)(z & 255u) + 127 - ew, 27) << 23), __int_as_float(max((int)(z >> 8) + 127 - ew, 27) << 23));
                }
                __syncwarp();
                if (lane == 0) mbar_arrive(sbase + B_S);
                TS(61, lane == 0);
                TW(28);
                BAR_SYNC(6, 384);
            }
        } else {
            const uint4* src = reinterpret_cast<const uint4*>(g_mod + (g & 3) * 1920 + 640) + (t - 320);
            uint4 w[10];
            mbar_wait(sbase + B_S, 0);
#pragma unroll 1
            for (int it = 0; it < SPIN_LIMIT; it++) {
                uint32_t bad = 0;
#pragma unroll
                for (int i = 0; i < 10; i++) w[i] = ld_rlx128(src + 64 * i);
#pragma unroll
                for (int i = 0; i < 10; i++) bad |= (w[i].y ^ ep) | (w[i].w ^ ep);
                if (!bad) break;
            }
            TS(60, t == 320);
            mbar_wait(sbase + B_S, 0);
            const uint32_t sc = lds4(sbase + SM_SCL + 8), sc1 = dup_lo(sc), sc2 = __byte_perm(sc, 0, 0x3232);
#pragma unroll
            for (int i = 0; i < 10; i++) {
                uint2 o = make_uint2(w[i].x, w[i].z);
                const int e = t - 320 + 64 * i;
                if (i < 8 && e < 480 && (uint32_t)(e % 60 - 16) >= 40u) o = make_uint2(hmul2(hmul2(o.x, sc1), sc2), hmul2(hmul2(o.y, sc1), sc2));
                reinterpret_cast<uint2*>(smem + SM_GA)[e] = o;
            }
            BAR_ARRIVE(2, 384);
            TS(62, t == 320);
            if (t == 352) {
                mbar_wait(sbase + B_Q, 1);
                asm volatile("fence.proxy.async.shared::cta;" ::: "memory");
                w1_issue(0, 12, sbase, j, &tw.m[0]);
            }
            __syncwarp();
        }
        if (st == 0 && (warp < 10 || (g == 127 && warp == 10))) {
            const bool cpath = g < 16 || warp == 10;
            float2 W[4][4];
            {
                const int p = r + 32 * q, f2 = g >> 4;
                const bool rev = !cpath && (g & 8);
                int P0[4], dP, dI = 14336;
                if (warp == 10) {
#pragma unroll
                    for (int i = 0; i < 4; i++) P0[i] = WB((i & 1) * 2 + (i >> 1)) + p * 16;
                    dP = 128;
                    dI = 2048;
                } else if (cpath) {
#pragma unroll
                    for (int i = 0; i < 4; i++) P0[i] = (i >> 1) * 6144 + p * 48 + (4 * (g & 1) + 2 * warp + (i & 1)) * 2;
                    dP = 384;
                    dI = 12288;
                } else {
#pragma unroll
                    for (int i = 0; i < 4; i++)
                        P0[i] = rev ? (127 - p) * 112 + (39 - bb0 - 5 * i + ((1 - f2) & 7)) * 2 : p * 112 + (bb0 + 5 * i + f2) * 2;
                    dP = rev ? -896 : 896;
                }
                TW(15);
                mbar_wait(sbase + B_W, 0);
                TW(16);
                const uint32_t sm = rev ? 0x80000000u : 0u;
#pragma unroll
                for (int u = 0; u < 4; u++)
#pragma unroll
                    for (int i = 0; i < 4; i++) {
                        const unsigned char* wp = smem + SM_W + P0[i] + u * dP;
                        const uint32_t a = *reinterpret_cast<const unsigned short*>(wp), b = *reinterpret_cast<const unsigned short*>(wp + dI);
                        W[i][u] = make_float2(__uint_as_float(a << 16), __uint_as_float(b * 65536u + sm));
                    }
                if (warp == 10 || (mir && warp == 0)) {
#pragma unroll
                    for (int i = 0; i < 4; i++) {
                        if (i && warp != 10) break;
#pragma unroll
                        for (int u = 0; u < 4; u++) {
                            const int pp = p + 8 * u;
                            const int o = warp == 10 ? WB((i & 1) * 2 + (i >> 1)) + ((128 - (i >> 1) - pp) & 127) * 16
                                                     : WB(2) + (rev ? pp * 16 + f2 * 2 : (127 - pp) * 16 + (8 - f2) * 2);
                            const unsigned char* q2 = smem + SM_W + o;
                            const uint32_t a = *reinterpret_cast<const unsigned short*>(q2), b = *reinterpret_cast<const unsigned short*>(q2 + 2048);
                            W[i][u].x = 0.5f * (W[i][u].x + __uint_as_float(a << 16));
                            W[i][u].y = 0.5f * (W[i][u].y + __uint_as_float(b * 65536u + (sm ^ 0x80000000u)));
                        }
                    }
                }
            }
            const uint32_t ft = sbase + SM_FT + 16 * lane, f1 = cpath ? 1024u : 0u;
            uint32_t B1[2][4][4], tw[2][4], B2[4], V[4][4], Wh[4][4];
#pragma unroll
            for (int n = 0; n < 4; n++) {
                lds16(B1[0][n], ft + 512 * n);
                lds16(B1[1][n], ft + 512 * n + 2 * f1);
            }
            lds16(tw[0], ft + 512 * 16);
            lds16(tw[1], ft + 512 * 16 + (f1 >> 1));
            lds16(B2, sbase + SM_B2 + 16 * lane);
            TW(17);
            {
                float mx = 0.f;
#pragma unroll
                for (int i = 0; i < 4; i++)
#pragma unroll
                    for (int u = 0; u < 4; u++) mx = fmaxf(mx, fmaxf(fabsf(W[i][u].x), fabsf(W[i][u].y)));
                const uint32_t e = min(__reduce_max_sync(0xffffffffu, __float_as_uint(mx)) >> 23, 248u);
                if (lane == 0) {
                    asm volatile("st.shared.u8 [%0], %1;" ::"r"(sbase + SM_WMX + warp), "r"(e) : "memory");
                    asm volatile("red.shared.max.u32 [%0], %1;" ::"r"(sbase + SM_WMX + 12), "r"(e) : "memory");
                    mbar_arrive(sbase + B_CH(4));
                }
                const float sw = pow2i(124 - (int)e);
#pragma unroll
                for (int i = 0; i < 4; i++)
#pragma unroll
                    for (int h = 0; h < 2; h++) {
                        Wh[i][h] = pack_h2(W[i][h].x * sw, W[i][h + 2].x * sw);
                        Wh[i][h + 2] = pack_h2(W[i][h].y * sw, W[i][h + 2].y * sw);
                        asm volatile("" : "+r"(Wh[i][h]), "+r"(Wh[i][h + 2]));
                    }
            }
            TS(35, t == 0);
            TW(18);
            if (warp == 9) {
                BAR_SYNC(10, 288);
                if (lane == 0) {
                    asm volatile("fence.proxy.async.shared::cta;" ::: "memory");
                    mbar_expect_tx(sbase + B_Q, 20480);
                    hint_wait2(&g_cnt[(g >> 4) * 32], hint1, sbase + SM_TW + 7840);
                    bulk_load(sbase + SM_T, g_I + g * 5120, 20480, sbase + B_Q);
                    TS(36, true);
                    TW(26);
                }
                __syncwarp();
            }
            const uint32_t go = lane * 160 + (warp < 10 ? 16 * (warp ^ ((r ^ (g >> 4)) & 1)) : 20480);
            char* gq = reinterpret_cast<char*>(g_I + g * 5120) + go;
            const uint32_t sq = sbase + SM_T + go;
            if (warp < 10) {
                TW(19);
                mbar_wait(sbase + B_Q, 0);
                TW(20);
#pragma unroll
                for (int jj = 0; jj < 4; jj++) lds16(V[jj], sq + 5120 * jj);
            } else {
                hint_wait(&g_cnt[0], hint1);
#pragma unroll
                for (int jj = 0; jj < 4; jj++) V[jj][0] = V[jj][1] = V[jj][2] = V[jj][3] = 0;
            }
#pragma unroll 1
            for (int it = 0; it < SPIN_LIMIT; it++) {
                uint32_t ok = 1, bad[4];
#pragma unroll
                for (int jj = 0; jj < 4; jj++) {
                    bad[jj] = ~((V[jj][0] & V[jj][1]) & (V[jj][2] & V[jj][3])) & 1;
                    ok &= ~bad[jj];
                }

                if (__all_sync(0xffffffffu, ok)) break;
#pragma unroll
                for (int jj = 0; jj < 4; jj++) reld128(V[jj], gq + 5120 * jj, bad[jj]);
            }
            TS(8, t == 0);
            TW(21);
            TS(21, t == 320);
            if (cpath) {
#pragma unroll
                for (int jj = 0; jj < 4; jj++)
#pragma unroll
                    for (int i = 0; i < 2; i++) {
                        const uint32_t z = V[jj][i], pm = warp == 10 ? z : V[jj][i + 2];
                        V[jj][i] = ffma2(pm, 0xbc003c00u, z);
                        V[jj][i + 2] = ffma2(pm, 0x3c00bc00u, z);
                    }
            }
            uint32_t X[4][4];
#pragma unroll
            for (int tl = 0; tl < 2; tl++) {
                uint32_t d[4][2];
#pragma unroll
                for (int n = 0; n < 4; n++) {
                    mma_g0(d[n], V[0][2 * tl], V[0][2 * tl + 1], V[1][2 * tl], V[1][2 * tl + 1], B1[tl][n][0], B1[tl][n][1]);
                    mma_g(d[n], V[2][2 * tl], V[2][2 * tl + 1], V[3][2 * tl], V[3][2 * tl + 1], B1[tl][n][2], B1[tl][n][3]);
                }
#pragma unroll
                for (int h = 0; h < 2; h++)
#pragma unroll
                    for (int cl = 0; cl < 2; cl++) {
                        X[2 * tl + cl][h] = movm(fms2(d[h][cl], tw[tl][2 * h], d[2 + h][cl], tw[tl][2 * h + 1]));
                        X[2 * tl + cl][2 + h] = movm(fmp2(d[h][cl], tw[tl][2 * h + 1], d[2 + h][cl], tw[tl][2 * h]));
                    }
            }
            TS(39, t == 0);
            TW(22);
#pragma unroll
            for (int n = 0; n < 4; n++) {
                lds16(B1[0][n], ft + 512 * (8 + n));
                lds16(B1[1][n], ft + 512 * (8 + n) + 2 * f1);
            }
            lds16(tw[0], ft + 512 * 18);
            lds16(tw[1], ft + 512 * 18 + (f1 >> 1));
            if (warp == 10) BAR_ARRIVE(4, 352);
#pragma unroll
            for (int i = 0; i < 4; i++) {
                uint32_t dr[2], di[2];
                mma_g0(dr, X[i][0], X[i][1], X[i][2], X[i][3], B2[0], B2[2]);
                mma_g0(di, X[i][0], X[i][1], X[i][2], X[i][3], B2[1], B2[0]);
                const uint32_t a0 = fms2(dr[0], Wh[i][0], di[0], Wh[i][2]), a1 = fms2(dr[1], Wh[i][1], di[1], Wh[i][3]);
                const uint32_t a2 = fmp2(dr[0], Wh[i][2], di[0], Wh[i][0]), a3 = fmp2(dr[1], Wh[i][3], di[1], Wh[i][1]);
                mma_g0(dr, a0, a1, a2, a3, B2[0], B2[1]);
                mma_g0(di, a0, a1, a2, a3, B2[2], B2[0]);
#pragma unroll
                for (int h = 0; h < 2; h++) {
                    X[i][h] = movm(fms2(dr[h], tw[i >> 1][2 * h], di[h], tw[i >> 1][2 * h + 1]));
                    X[i][2 + h] = movm(fmp2(dr[h], tw[i >> 1][2 * h + 1], di[h], tw[i >> 1][2 * h]));
                }
            }
            const uint32_t sg = cpath ? 0x80000000u : 0u;
            TS(40, t == 0);
            TW(23);
#pragma unroll
            for (int n = 0; n < 4; n++) {
                uint32_t d[2][2];
#pragma unroll
                for (int tl = 0; tl < 2; tl++) {
                    mma_g0(d[tl], X[2 * tl][0], X[2 * tl + 1][0], X[2 * tl][1], X[2 * tl + 1][1], B1[tl][n][0], B1[tl][n][1]);
                    mma_g(d[tl], X[2 * tl][2], X[2 * tl + 1][2], X[2 * tl][3], X[2 * tl + 1][3], B1[tl][n][2], B1[tl][n][3]);
                }
                if (cpath) {
#pragma unroll
                    for (int u = 0; u < 2; u++) {
                        const uint32_t a = d[0][u], b = d[1][u];
                        d[0][u] = fadd2(a, b);
                        d[1][u] = fsub2(a, b);
                    }
                }
                uint32_t o[4];
#pragma unroll
                for (int i = 0; i < 4; i++) {
                    o[i] = (d[i >> 1][i & 1] ^ (i >> 1 ? sg : 0u)) & 0xfffefffeu;
                }
                if (warp < 10) sts16(sq + 5120 * n, o[0], o[1], o[2], o[3]);
                else st_rlx128(reinterpret_cast<uint4*>(gq + 5120 * n), o[0], o[1], o[2], o[3]);
            }
            TS(9, t == 0);
            TW(24);
            TS(22, t == 320);
            if (warp == 10) {
                __syncwarp();
                if (lane < NR) red_add(&g_cnt[(8 + lane) * 32]);
            } else {
                asm volatile("cp.async.bulk.wait_group 0;" ::: "memory");
                if (warp < 9) {
                    asm volatile("bar.arrive 4, %0;" ::"r"(g == 127 ? 352 : 320) : "memory");
                } else {
                    asm volatile("bar.sync 4, %0;" ::"r"(g == 127 ? 352 : 320) : "memory");
                    if (lane == 0) {
                        asm volatile("fence.proxy.async.shared::cta;" ::: "memory");
                        asm volatile("cp.async.bulk.global.shared::cta.bulk_group [%0], [%1], 20480;"
                                     ::"l"(g_I + g * 5120), "r"(sbase + SM_T) : "memory");
#pragma unroll
                        for (int i = 0; i < NR; i++)
                            asm volatile("cp.reduce.async.bulk.global.shared::cta.bulk_group.add.u32 [%0], [%1], 16;"
                                         ::"l"(&g_cnt[(8 + i) * 32]), "r"(sbase + SM_ONE) : "memory");
                        asm volatile("cp.async.bulk.commit_group;" ::: "memory");
                        TW(29);
                        TS(45, true);
                        TW(25);
                    }
                    __syncwarp();
                }
            }
        }
    }

    {
    int t;
    asm volatile("mov.u32 %0, %%tid.x;" : "=r"(t));
    const int lane = t & 31, warp = __shfl_sync(0xffffffffu, t >> 5, 0), q = lane & 3, r = lane >> 2;
    const uint32_t xoff = (lane & 15) * XP + (lane >> 4) * 16;
    if (warp < 8) {
        const uint32_t xt = sbase + SM_XT + warp * 160 + xoff, mva = sbase + SM_GA + warp * 480 + 16 * q;
        uint32_t mv[32], x1[5][4], ah[4], al[4];
        lds16(ah, sbase + SM_TS + 16 * lane);
        lds16(al, sbase + SM_TS + 512 + 16 * lane);
#pragma unroll
        for (int ks = 0; ks < 5; ks++) ldsm4(x1[ks], xt + 32 * ks);
#pragma unroll
        for (int i = 0; i < 7; i++) lds16(mv + 4 * i, mva + 64 * i);
        asm volatile("ld.shared.v2.b32 {%0,%1}, [%2];" : "=r"(mv[28]), "=r"(mv[29]) : "r"(mva + 448 - 8 * q));
        BAR_SYNC(5, 256);
        TS(12, t == 0);
        TW(37);
        const uint32_t* zs = reinterpret_cast<const uint32_t*>(smem + SM_T + q * PT) + warp * 80 + r;
        float sd[4] = {0.f, 0.f, 0.f, 0.f}, g1[4] = {0.f, 0.f, 0.f, 0.f}, g2[4] = {0.f, 0.f, 0.f, 0.f};
        uint32_t K0 = 0, K1 = 0;
#pragma unroll
        for (int ks = 0; ks < 5; ks++) {
#pragma unroll
            for (int tt = 0; tt < 2; tt++) {
                const uint32_t z0 = zs[16 * ks + 8 * tt], z1 = zs[PT + 16 * ks + 8 * tt];
                float d[4];
                mma_h0(d, al[0], al[1], al[2], al[3], z0, z1);
                mma_h(d, ah[0], ah[1], ah[2], ah[3], z0, z1);
                const uint32_t ga2 = mv[ks < 4 ? 2 * ks + tt : 28 + tt];
                x1[ks][2 * tt] = hadd2(x1[ks][2 * tt], hmul2(ga2, pack_bf2(d[0], d[1])));
                x1[ks][2 * tt + 1] = hadd2(x1[ks][2 * tt + 1], hmul2(ga2, pack_bf2(d[2], d[3])));
            }
            if (ks == 0) {
                K0 = dup_lo(__shfl_sync(0xffffffffu, x1[0][0], lane & 28));
                K1 = dup_lo(__shfl_sync(0xffffffffu, x1[0][1], lane & 28));
            }
            ln_mma(x1[ks], K0, K1, sd, g1, g2);
        }
        const uint32_t red = sbase + SM_RED + 128 * r;
        if (q == (r >> 1)) {
            const float Q0 = (r & 1) ? g1[1] : g1[0], Q1 = (r & 1) ? g2[3] : g2[2];
            const uint32_t a = red + ((8 * warp) ^ (16 * (r & 1)));
            asm volatile("st.shared.v2.f32 [%0], {%1,%2};" ::"r"(a), "f"(fmaf(80.f, bf_lo(K0), sd[0])), "f"(fmaf(sd[0] * sd[0], -1.0f / 80.0f, Q0)) : "memory");
            asm volatile("st.shared.v2.f32 [%0], {%1,%2};" ::"r"(a + 64), "f"(fmaf(80.f, bf_lo(K1), sd[2])), "f"(fmaf(sd[2] * sd[2], -1.0f / 80.0f, Q1)) : "memory");
        }
        uint32_t ra = red + 64 * (q & 1) + 32 * (q >> 1) + 16 * (r & 1);
        uint32_t s0 = (q & 1) ? 0x5454u : 0x1010u, s1 = s0 ^ 0x4444u;
        uint4* hp = g_H + (g * 40 + warp * 5) * 32 + lane;
        asm volatile("" : "+r"(ra), "+r"(s0), "+r"(s1), "+l"(hp));
        TW(38);
        BAR_SYNC(7, 288);
        TS(13, t == 0);
        TW(39);
        if (warp >= 4) {
            uint32_t k0, k1;
            asm volatile("mov.u32 %0, %%clock;" : "=r"(k0));
#pragma unroll
            for (int ks = 0; ks < 5; ks++) stsm4(xt + 32 * ks, x1[ks]);
#pragma unroll 1
            for (int i = 0; i < 1000; i++) {
                asm volatile("mov.u32 %0, %%clock;" : "=r"(k1));
                if (k1 - k0 >= HD) break;
            }
        }
        uint32_t m0, m1, h0, h1, l0, l1;
        {
            uint32_t p[8];
            lds16(p, ra);
            lds16(p + 4, ra ^ 16);
            const float a0 = __uint_as_float(p[0]), a1 = __uint_as_float(p[2]), a2 = __uint_as_float(p[4]), a3 = __uint_as_float(p[6]);
            const float S = (a0 + a1) + (a2 + a3), mh = S * 0.25f;
            const float S2 = __shfl_xor_sync(0xffffffffu, S, 2);
            const float e0 = a0 - mh, e1 = a1 - mh, e2 = a2 - mh, e3 = a3 - mh;
            const float M = fmaf(fmaf(e0, e0, e1 * e1) + fmaf(e2, e2, e3 * e3), 1.0f / 80.0f,
                                 (__uint_as_float(p[1]) + __uint_as_float(p[3])) + (__uint_as_float(p[5]) + __uint_as_float(p[7])));
            const float M2 = __shfl_xor_sync(0xffffffffu, M, 2);
            const uint32_t mb = pack_bf2((S + S2) * (1.0f / 640.0f), 0.f);
            const uint32_t mo = __shfl_xor_sync(0xffffffffu, mb, 1);
            const float var = bf_round(fmaf((S - S2) * (S - S2), 1.0f / 640.0f, M + M2) * (1.0f / 640.0f));
            const float rs = rcpf(bf_round(sqrtf_a(bf_round(var + 1e-5f))));
            const uint32_t rr = pack_bf2(rs, rs - bf_round(rs));
            const uint32_t ro = __shfl_xor_sync(0xffffffffu, rr, 1);
            m0 = __byte_perm(mb, mo, s0);
            m1 = __byte_perm(mb, mo, s1);
            h0 = __byte_perm(rr, ro, s0);
            h1 = __byte_perm(rr, ro, s1);
            l0 = __byte_perm(rr, ro, s0 + 0x2222u);
            l1 = __byte_perm(rr, ro, s1 + 0x2222u);
        }
#pragma unroll
        for (int ks = 0; ks < 5; ks++) {
            uint32_t o[4];
#pragma unroll
            for (int tt = 0; tt < 2; tt++) {
                const uint2 cs = make_uint2(mv[18 + 2 * ks + tt], mv[8 + 2 * ks + tt]);
                const uint32_t e0 = hsub2(x1[ks][2 * tt], m0), e1 = hsub2(x1[ks][2 * tt + 1], m1);
                o[2 * tt] = hfma2(hfma2(e0, h0, hmul2(e0, l0)), cs.x, cs.y);
                o[2 * tt + 1] = hfma2(hfma2(e1, h1, hmul2(e1, l1)), cs.x, cs.y);
            }
            const uint32_t mk = ((o[0] ^ tag) & 1u) * 3u;
            asm volatile("st.relaxed.gpu.global.v4.b32 [%0], {%1,%2,%3,%4};"
                         ::"l"(hp + 32 * ks), "r"((o[0] & ~mk) | (mk & (2u - tag))), "r"(o[1]), "r"(o[2]), "r"(o[3]) : "memory");
        }
        if (warp < 4) {
#pragma unroll
            for (int ks = 0; ks < 5; ks++) stsm4(xt + 32 * ks, x1[ks]);
        }
        __syncwarp();
        if (lane == 0) mbar_arrive(sbase + B_CH(0));
        TS(14, t == 0);
        TW(40);
    }

    int c0, c1;
    if (warp < 8) {
        asm volatile("setmaxnreg.inc.sync.aligned.u32 216;");
        const int gw = (g & ~7) + warp;
        const uint4* hsrc = g_H + gw * 1280 + lane;
        uint32_t A[2][5][8];
        {
            uint32_t k0, k1;
            asm volatile("mov.u32 %0, %%clock;" : "=r"(k0));
            const uint32_t dl = warp < 4 ? AD0 : AD1;
#pragma unroll 1
            for (int i = 0; i < 1000; i++) {
                asm volatile("mov.u32 %0, %%clock;" : "=r"(k1));
                if (k1 - k0 >= dl) break;
            }
        }
        ld_frag(A[0][0], hsrc);
#pragma unroll
        for (int i = 1; i < 5; i++) ld_frag(A[0][i], hsrc + i * 64);
        TS(15, t == 0);
        TW(41);
        float acc[96];
        const uint32_t dB32 = ((sbase & 0x3FFFF) >> 4) | (4096 >> 4 << 16);
        const uint32_t dB48 = ((sbase & 0x3FFFF) >> 4) | (6144 >> 4 << 16);
        const uint32_t rbase = mapa(sbase, (g & 1) ^ 1);
        if (warp >= 4) BAR_SYNC(1, 256);
#pragma unroll 1
        for (int o = 0; o < 20; o += 10) {
#pragma unroll
            for (int hb = 0; hb < 2; hb++) {
                const uint4* hp = hsrc + (o + 5 * hb) * 64;
                TC((warp >> 2) * 128 + (o + 5 * hb) * 4, (t & 127) == 0);
#pragma unroll 1
                for (int s = 0; s < SPIN_LIMIT; s++) {
                    uint32_t bad[5];
#pragma unroll
                    for (int i = 0; i < 5; i++) bad[i] = ((A[hb][i][0] ^ tag) | (A[hb][i][4] ^ tag)) & 1;
                    if (!__any_sync(0xffffffffu, bad[0] | bad[1] | bad[2] | bad[3] | bad[4])) break;
#pragma unroll
                    for (int i = 0; i < 5; i++) reld_frag(A[hb][i], hp + i * 64, bad[i]);
                }
                settle_frags(A[hb]);
                TS(16, t == 0 && o + hb == 0);
#pragma unroll
                for (int bi = 0; bi < 5; bi++) {
                    const int it = o + 5 * hb + bi, slot = it & 15;
                    TC((warp >> 2) * 128 + it * 4 + 1, (t & 127) == 0);
                    mbar_wait(sbase + B_FULL(slot), (it >> 4) & 1);
                    TC((warp >> 2) * 128 + it * 4 + 2, (t & 127) == 0);
                    const uint32_t db = dB32 + slot * (SLOT >> 4);
                    wg_fence();
                    wgmma_n192_rs(acc, A[hb][bi], db, it != 0);
                    wgmma_n192_rs(acc, A[hb][bi] + 4, db + 128, 1);
                    wg_commit();
                    if (5 * hb + bi == (STAG - 1) % 10 && it == STAG - 1 && warp < 4) BAR_ARRIVE(1, 256);
                    wg_wait<1>();
                    TC((warp >> 2) * 128 + it * 4 + 3, (t & 127) == 0);
                    if (5 * hb + bi == 8) {
                        if (lane == 0) mbar_arrive_cl(o == 0 ? rbase + B_CH(1) : sbase + B_EMPTY(1));
                    } else if (it > 0 && lane == 0) mbar_arrive(sbase + B_EMPTY((it - 1) & 15));
                    if (bi == 0) {
#pragma unroll
                        for (int i = 0; i < 5; i++) reld_frag(A[hb ^ 1][i], hp + (5 + i) * 64, hb == 0 || o == 0);
                    }
                }
            }
        }
        wg_wait<0>();
        if (lane == 0) mbar_arrive(sbase + B_EMPTY(3));
        TS(17, t == 0);
        TS(41, t == 128);

        uint4* pdst = g_P + (gw * 8 + j) * 640 + lane;
        unsigned int* pcnt = g_cntP + gw * 40;
        const uint32_t tag16 = tag << 16;
        const uint32_t loc = (warp ^ j) < 2, obase = mapa(sbase, warp & 1), ldst = obase + (j & 1) * 512 + lane * 16;
        if (t < 3) mbar_expect_tx(sbase + B_FULL(4 + t), t < 2 ? 8192 : 4096);
        const uint32_t land = 4 * SLOT + warp * 6144 + lane * 16, xbar = B_X(warp & 4);
        uint32_t a[48], b[2][12];
        float acc2[2][64];
        mbar_wait(sbase + B_CH(1), 0);
#pragma unroll
        for (int s = 0; s < 4; s++) {
            const int slot = 8 + s;
            TC(256 + (warp >> 2) * 128 + s * 4 + 1, (t & 127) == 0);
            mbar_wait(sbase + B_FULL(slot), 1);
            TC(256 + (warp >> 2) * 128 + s * 4 + 2, (t & 127) == 0);
            const uint32_t db = dB48 + slot * (SLOT >> 4);
#pragma unroll
            for (int ks = 0; ks < 3; ks++) {
                const int jj = 11 - 3 * s - ks;
                silu4(acc + 8 * jj, a[4 * jj], a[4 * jj + 1]);
                silu4(acc + 8 * jj + 4, a[4 * jj + 2], a[4 * jj + 3]);
                st_async16(rbase + land + 512 * jj, a + 4 * jj, rbase + xbar + 8 * s);
                wg_fence();
                wgmma_n128_rs(acc2[0], a + 4 * jj, db + 128 * (2 - ks), jj != 11);
                wg_commit();
                if (ks == 0 && s > 0) {
                    wg_wait<1>();
                    if (lane == 0) mbar_arrive(sbase + B_EMPTY(slot - 1));
                }
            }
        }
        TS(18, t == 0);
        TS(42, t == 128);
        mbar_wait(sbase + xbar, 1);
#pragma unroll
        for (int ks = 0; ks < 3; ks++) lds16(b[0] + 4 * ks, sbase + land + 512 * (9 + ks));
#pragma unroll
        for (int tl = 4; tl < 16; tl++) {
            const int s = tl & 3, slot = tl < 8 ? 8 + tl : (tl < 12 ? tl - 8 : tl - 4);
            const bool own = (tl >> 2) == 2;
            TC(256 + (warp >> 2) * 128 + tl * 4 + 1, (t & 127) == 0);
            mbar_wait(sbase + B_FULL(slot), tl < 8);
            TC(256 + (warp >> 2) * 128 + tl * 4 + 2, (t & 127) == 0);
            const uint32_t db = dB48 + slot * (SLOT >> 4);
            wg_fence();
#pragma unroll
            for (int ks = 0; ks < 3; ks++)
                wgmma_n128_rs(acc2[tl >> 3], own ? a + 4 * (9 - 3 * s + ks) : b[s & 1] + 4 * ks, db + 128 * ks, tl != 8 || ks != 0);
            wg_commit();
            if (!own || s < 2) wg_wait<1>();
            if (tl <= 8 && lane == 0) mbar_arrive(sbase + B_EMPTY(7 + tl));
            if (tl == 9 && lane == 0) {
                mbar_arrive(sbase + B_EMPTY(0));
                mbar_arrive_cl(rbase + B_CH(2));
            }
            TC(256 + (warp >> 2) * 128 + tl * 4 + 3, (t & 127) == 0);
            if (tl < 7) mbar_wait(sbase + xbar + 8 * (s + 1), 1);
            TC(256 + (warp >> 2) * 128 + tl * 4 + 4, (t & 127) == 0);
            if ((!own && s < 3) || tl == 11) {
                const int sn = (s + 1) & 3;
#pragma unroll
                for (int ks = 0; ks < 3; ks++) lds16(b[sn & 1] + 4 * ks, sbase + land + 512 * (9 - 3 * sn + ks));
            }
            if (tl >= 8 && tl < 8 + 8 / SP0) {
                send_chunk<SP0>(acc2[0] + 8 * SP0 * (tl - 8), pdst + 32 * SP0 * (tl - 8), tag16, loc, ldst + LP(0) + 1024 * SP0 * (tl - 8), obase + B_FULL(4));
                if (tl == 7 + 8 / SP0) {
                    __syncwarp();
                    if (lane == 0 && !loc) red_add(pcnt);
                    TS(19, t == 0);
                    TS(43, t == 128);
                }
            }
        }
#pragma unroll
        for (int v = 0; v < 8; v++) {
            const int slot = 12 + (v >> 1);
            TC(256 + (warp >> 2) * 128 + (16 + v) * 4 + 1, (t & 127) == 0);
            if (!(v & 1)) mbar_wait(sbase + B_FULL(slot), 0);
            TC(256 + (warp >> 2) * 128 + (16 + v) * 4 + 2, (t & 127) == 0);
            const uint32_t db = dB48 + slot * (SLOT >> 4) + (v & 1) * 384;
            wg_fence();
#pragma unroll
            for (int ks = 0; ks < 3; ks++)
                wgmma_n64_rs(acc2[0], v < 4 ? a + 4 * (3 * v + ks) : b[v & 1] + 4 * ks, db + 128 * ks, (v | ks) != 0);
            wg_commit();
            if (v == 0 || v >= 4) wg_wait<1>();
            if (v >= 2 && v < 7 && v != 3) {
                const int vn = v == 2 ? 4 : v + 1;
#pragma unroll
                for (int ks = 0; ks < 3; ks++) lds16(b[vn & 1] + 4 * ks, sbase + land + 512 * (3 * (vn - 4) + ks));
            }
            if (v == 0) {
                if (loc) {
                    mbar_wait(sbase + B_EMPTY(0), 0);
                    mbar_wait(sbase + B_CH(2), 0);
                }
            }
            if (v == HV2 && lane == 0 && !loc) red_add(pcnt + 16);
            if (v < 8 / SP1) {
                send_chunk<SP1>(acc2[1] + 8 * SP1 * v, pdst + 256 + 32 * SP1 * v, tag16, loc, ldst + LP(1) + 1024 * SP1 * v, obase + B_FULL(5));
                if (v == 8 / SP1 - 1) {
                    __syncwarp();
                    if (lane == 0 && !loc) red_add(pcnt + 8);
                    TS(20, t == 0);
                    TS(44, t == 128);
                }
            }
        }
        wg_wait<0>();
        TS(23, t == 0);
        TW(61);
        TS(46, t == 128);
        send_chunk<4>(acc2[0], pdst + 512, tag16, loc, ldst + LP(2), obase + B_FULL(6));
        __syncwarp();
        if (HV2 == 8 && lane == 0 && !loc) red_add(pcnt + 16);
        TS(24, t == 0);
        TW(60);
        TS(47, t == 128);
        c0 = warp < 4 ? 4 : 3;
        c1 = c0 + 1;
    } else {
        asm volatile("barrier.cluster.wait.acquire.aligned;" ::: "memory");
        asm volatile("setmaxnreg.dec.sync.aligned.u32 72;");
        c0 = 0;
        c1 = 3;
        if (warp == 11) {
            const int tl = lane - 8;
            const int slot = tl < 0 ? (lane + 12) & 15 : (tl < 8 ? 8 + tl : (tl < 12 ? tl - 8 : tl - 4));
            const CUtensorMap* tm = &tw.m[(tl >= 0) + (tl >= 16)];
            const int cr = tl < 0 ? 32 * (lane + 12)
                                  : (tl < 16 ? 192 * (j ^ ((tl >> 2) & 1)) + 144 - 48 * (tl & 3) : 192 * (j ^ ((tl >> 1) & 1)) + 96 * (tl & 1));
            const int cb = tl < 0 ? 3 * j : 5 * (j & 1) + 2 * (tl >> 3);
            const uint32_t bar = sbase + B_FULL(slot);
            BAR_SYNC(7, 288);
            {
                uint32_t k0, k1;
                asm volatile("mov.u32 %0, %%clock;" : "=r"(k0));
#pragma unroll 1
                for (int i = 0; i < 1000; i++) {
                    asm volatile("mov.u32 %0, %%clock;" : "=r"(k1));
                    if (k1 - k0 >= WD) break;
                }
            }
            asm volatile("fence.proxy.async.shared::cta;" ::: "memory");
            __syncwarp();
#pragma unroll 1
            for (int n = 0; n < 28; n++) {
                if (lane == n) {
                    if (n >= 4) mbar_wait(bar + 8, tl >= 8);
                    mbar_expect_tx(bar, SLOT);
                    tma_load3(sbase + slot * SLOT, tm, cr, cb, bar);
                    TC(80 + n, true);
                }
                __syncwarp();
            }
        }
    }
    mbar_wait(sbase + B_CH(0), 0);
#pragma unroll 1
    for (int cc = c0; cc < c1; cc++) {
        const int u = cc < 2 ? 2 * (warp & 3) + cc : 4 * cc + (warp & 3);
        if (warp >= 8 && cc != 1) hint_wait(g_cntP + g * 40 + 8 * (cc >> 1), ep * 6u - (cc == 0 ? HP0 : HP1));
        uint32_t xv[2][4], gb[2][2], w[3][8];
#pragma unroll
        for (int hh = 0; hh < 2; hh++) {
            ldsm4(xv[hh], sbase + SM_XT + (u + 20 * hh) * 32 + xoff);
            gb[hh][0] = lds4(sbase + SM_GB + 32 * (u + 20 * hh) + 4 * q);
            gb[hh][1] = lds4(sbase + SM_GB + 32 * (u + 20 * hh) + 4 * q + 16);
        }
        uint32_t* op = reinterpret_cast<uint32_t*>(out + (size_t)(g + 128 * r) * 640 + 16 * u + 2 * q);
        const uint4* src[3];
#pragma unroll
        for (int s = 0; s < 3; s++) src[s] = g_P + (g * 8 * 20 + u) * 32 + lane + (((j >> 1) + 1 + s) & 3) * 1280;
        asm volatile("{\n.reg .pred p;\nsetp.eq.u32 p, %4, 0;\n@p prefetch.global.L2 [%0];\n@p prefetch.global.L2 [%1];\n"
                     "@p prefetch.global.L2 [%2];\n@p st.global.b32 [%3], %4;\n}\n"
                     ::"l"(src[0]), "l"(src[1]), "l"(src[2]), "l"(op), "r"(ep) : "memory");
        const uint32_t la = sbase + LP(cc >> 1) + (u & 7) * 1024 + lane * 16;
        mbar_wait(sbase + B_FULL(4 + (cc >> 1)), 1);
        lds16(w[0], la);
        lds16(w[0] + 4, la + 512);
        float d[2][2][4];
#pragma unroll
        for (int hh = 0; hh < 2; hh++) {
#pragma unroll
            for (int i = 0; i < 4; i++) {
                d[hh][i >> 1][2 * (i & 1)] = bf_lo(i ? w[0][4 * hh + i] : w[0][4 * hh] & 0xfffeu);
                d[hh][i >> 1][2 * (i & 1) + 1] = bf_hi(w[0][4 * hh + i]);
                asm volatile("" : "+f"(d[hh][i >> 1][2 * (i & 1)]), "+f"(d[hh][i >> 1][2 * (i & 1) + 1]));
            }
        }
        if (warp < 8) hint_wait(g_cntP + g * 40 + 8 * (cc >> 1), ep * 6u - (cc < 4 ? HP1 : HP2));
        TS(48 + cc, (t & 127) == 0);
        TW(57);
#pragma unroll
        for (int s = 0; s < 3; s++) ld_frag<10240>(w[s], src[s]);
#pragma unroll 1
        for (int it = 0; it < SPIN_LIMIT; it++) {
            uint32_t bad[3];
#pragma unroll
            for (int s = 0; s < 3; s++) bad[s] = ((w[s][0] ^ tag) | (w[s][4] ^ tag)) & 1;
            TV(52 + cc, g_tw[(blockIdx.x * 12) * 64] + 1000 * it + 1);
            if (!__any_sync(0xffffffffu, bad[0] | bad[1] | bad[2])) break;
#pragma unroll
            for (int s = 0; s < 3; s++) reld_frag<10240>(w[s], src[s], bad[s]);
        }
        TS(53 + cc, (t & 127) == 0);
        TW(58);
#pragma unroll
        for (int hh = 0; hh < 2; hh++) {
#pragma unroll
            for (int s = 0; s < 3; s++) {
#pragma unroll
                for (int i = 0; i < 4; i++) {
                    d[hh][i >> 1][2 * (i & 1)] += bf_lo(i ? w[s][4 * hh + i] : w[s][4 * hh] & 0xfffeu);
                    d[hh][i >> 1][2 * (i & 1) + 1] += bf_hi(w[s][4 * hh + i]);
                }
            }
#pragma unroll
            for (int k = 0; k < 4; k++)
                op[(k & 1) * (8 * 128 * 320) + (k >> 1) * 4 + 160 * hh] =
                    hadd2(xv[hh][k], hmul2(gb[hh][k >> 1], pack_bf2(d[hh][k >> 1][2 * (k & 1)], d[hh][k >> 1][2 * (k & 1) + 1])));
        }
    }
    }
    if (g == 0 && t < 32) asm volatile("st.relaxed.gpu.global.u32 [%0], %1;" ::"l"(g_epoch + t), "r"(ep) : "memory");
    TS(25, t == 0);
    TW(59);
    TS(26, t == 256);
}

typedef CUresult (*EncodeFn)(CUtensorMap*, CUtensorMapDataType, cuuint32_t, void*, const cuuint64_t*, const cuuint64_t*,
                             const cuuint32_t*, const cuuint32_t*, CUtensorMapInterleave, CUtensorMapSwizzle,
                             CUtensorMapL2promotion, CUtensorMapFloatOOBfill);

static void make_map(EncodeFn enc, CUtensorMap* m, const void* base, int rows, int cols, int box_rows, int box_blks) {
    cuuint64_t dims[3] = {64, (cuuint64_t)rows, (cuuint64_t)(cols / 64)};
    cuuint64_t strides[2] = {(cuuint64_t)cols * 2, 128};
    cuuint32_t box[3] = {64, (cuuint32_t)box_rows, (cuuint32_t)box_blks};
    cuuint32_t es[3] = {1, 1, 1};
    enc(m, CU_TENSOR_MAP_DATA_TYPE_BFLOAT16, 3, const_cast<void*>(base), dims, strides, box, es,
        CU_TENSOR_MAP_INTERLEAVE_NONE, CU_TENSOR_MAP_SWIZZLE_128B, CU_TENSOR_MAP_L2_PROMOTION_L2_256B,
        CU_TENSOR_MAP_FLOAT_OOB_FILL_NONE);
}

static void make_fmap(EncodeFn enc, CUtensorMap* m, const void* base, int box_cols) {
    cuuint64_t dims[2] = {16 * 321, 128};
    cuuint64_t strides[1] = {16 * 321 * 2};
    cuuint32_t box[2] = {(cuuint32_t)box_cols, 128};
    cuuint32_t es[2] = {1, 1};
    enc(m, CU_TENSOR_MAP_DATA_TYPE_BFLOAT16, 2, const_cast<void*>(base), dims, strides, box, es,
        CU_TENSOR_MAP_INTERLEAVE_NONE, CU_TENSOR_MAP_SWIZZLE_NONE, CU_TENSOR_MAP_L2_PROMOTION_NONE,
        CU_TENSOR_MAP_FLOAT_OOB_FILL_NONE);
}

extern "C" void kernel_launch(void* const* d_in, const int* in_sizes, int n_in, void* d_out, int out_size) {
    const bf16* x = (const bf16*)d_in[0];
    const bf16* wr = (const bf16*)d_in[1];
    const bf16* wi = (const bf16*)d_in[2];
    const bf16* w1 = (const bf16*)d_in[4];
    const bf16* w2 = (const bf16*)d_in[5];
    const bf16* c = (const bf16*)d_in[6];
    const bf16* wmod = (const bf16*)d_in[7];
    bf16* out = (bf16*)d_out;
    static EncodeFn enc = nullptr;
    static Scratch* scr = nullptr;
    static const uint32_t* gt = nullptr;
    static Map3 tw;
    static const void *pw1 = nullptr, *pw2 = nullptr, *pwr = nullptr, *pwi = nullptr, *pwm = nullptr;
    if (!enc) {
        cudaFuncSetAttribute(fused_kernel, cudaFuncAttributeMaxDynamicSharedMemorySize, SMEM_TOTAL);
        void* fn = nullptr;
        cudaDriverEntryPointQueryResult qr;
        cudaGetDriverEntryPoint("cuTensorMapEncodeTiled", &fn, cudaEnableDefault, &qr);
        enc = (EncodeFn)fn;
        cudaGetSymbolAddress((void**)&scr, g_s);
        cudaGetSymbolAddress((void**)&gt, g_tab);
        void* pi = g_I;
        cuuint64_t dims[2] = {5120, 129};
        cuuint64_t strides[1] = {20480};
        cuuint32_t box[2] = {40, 129};
        cuuint32_t es[2] = {1, 1};
        enc(&tq, CU_TENSOR_MAP_DATA_TYPE_UINT32, 2, pi, dims, strides, box, es, CU_TENSOR_MAP_INTERLEAVE_NONE,
            CU_TENSOR_MAP_SWIZZLE_NONE, CU_TENSOR_MAP_L2_PROMOTION_NONE, CU_TENSOR_MAP_FLOAT_OOB_FILL_NONE);
        box[1] = 16;
        enc(&tq16, CU_TENSOR_MAP_DATA_TYPE_UINT32, 2, pi, dims, strides, box, es, CU_TENSOR_MAP_INTERLEAVE_NONE,
            CU_TENSOR_MAP_SWIZZLE_NONE, CU_TENSOR_MAP_L2_PROMOTION_NONE, CU_TENSOR_MAP_FLOAT_OOB_FILL_NONE);
    }
    if (pw1 != w1 || pw2 != w2) {
        make_map(enc, &tw.m[0], w1, 640, 1536, 32, 3);
        make_map(enc, &tw.m[1], w2, 1536, 640, 48, 2);
        make_map(enc, &tw.m[2], w2, 1536, 640, 96, 1);
        pw1 = w1;
        pw2 = w2;
    }
    if (pwm != wmod) {
        cuuint64_t dims[2] = {3840, 640};
        cuuint64_t strides[1] = {7680};
        cuuint32_t box[2] = {16, 160};
        cuuint32_t es[2] = {1, 1};
        enc(&tw.m[11], CU_TENSOR_MAP_DATA_TYPE_BFLOAT16, 2, const_cast<bf16*>(wmod), dims, strides, box, es, CU_TENSOR_MAP_INTERLEAVE_NONE,
            CU_TENSOR_MAP_SWIZZLE_32B, CU_TENSOR_MAP_L2_PROMOTION_NONE, CU_TENSOR_MAP_FLOAT_OOB_FILL_NONE);
        pwm = wmod;
    }
    if (pwr != wr || pwi != wi) {
        make_fmap(enc, &tfa_r, wr, 56);
        make_fmap(enc, &tfa_i, wi, 56);
        make_fmap(enc, &tfb_r, wr, 8);
        make_fmap(enc, &tfb_i, wi, 8);
        make_fmap(enc, &tfc_r, wr, 24);
        make_fmap(enc, &tfc_i, wi, 24);
        pwr = wr;
        pwi = wi;
    }
    fused_kernel<<<128, 384, SMEM_TOTAL, cudaStreamPerThread>>>(x, c, wmod, scr, gt, out, w1, tw);
}
```
